```python
import torch

def _softmax(x, axis=-1):
    return torch.softmax(x, dim=axis)
def _gelu(x):
    return torch.nn.functional.gelu(x, approximate="tanh")
def _silu(x):
    return torch.nn.functional.silu(x)
def _sigmoid(x):
    return torch.sigmoid(x)
def _layernorm(x, axis=-1, eps=1e-5):
    m = x.mean(dim=axis, keepdim=True)
    v = x.var(dim=axis, keepdim=True, unbiased=False)
    return (x - m) / torch.sqrt(v + eps)
def _scatter_add(tgt, idx, src, axis=0):
    return tgt.clone().index_add_(axis, idx, src)
def _segment_sum(src, seg, n):
    out = torch.zeros((n,) + src.shape[1:], dtype=src.dtype)
    return out.index_add_(0, seg, src)
def _pad(x, pw):
    flat = tuple(v for pair in reversed(pw) for v in pair)
    return torch.nn.functional.pad(x, flat)

kernel_name = 'concat_heads__ssm_conv_h3__ssm_conv_s4__prompt'

def setup_inputs():

    _w = (lambda a: (lambda t: t.to(torch.bfloat16) if t.is_floating_point() else t)(torch.as_tensor(a)))
    def _A_setup():
        B, S, D = 1, 2048, 448
        ks = 4
        return {
            "q": _w((lambda *s: torch.randn(*s, dtype=torch.bfloat16) * 0.05)(B, S, D)),
            "k": _w((lambda *s: torch.randn(*s, dtype=torch.bfloat16) * 0.4)(B, S, D)),
            "v": _w((lambda *s: torch.randn(*s, dtype=torch.bfloat16) * 0.4)(B, S, D)),
            "shift_k": _w((lambda *s: torch.randn(*s, dtype=torch.bfloat16) * 0.4)(D, ks) * 0.5),
            "ssm_k": _w((lambda *s: torch.randn(*s, dtype=torch.bfloat16) * 0.4)(D, S) * (1.0 / S ** 0.5)),
            "ssm_D": _w((lambda *s: torch.randn(*s, dtype=torch.bfloat16) * 0.4)(D)),
        }
    _A_in = _A_setup()

    def _B_setup():
        B, L, D, N = 1, 2048, 448, 256
        A_re = -(lambda _x: torch.exp(torch.as_tensor(_x)))((lambda *s: torch.randn(*s, dtype=torch.bfloat16) * 6.4)(D, N))
        A_im = torch.pi * (lambda *s: torch.randn(*s, dtype=torch.bfloat16) * 0.05)(D, N)
        B_re = (lambda *s: torch.randn(*s, dtype=torch.bfloat16) * 0.1)(D, N)
        B_im = (lambda *s: torch.randn(*s, dtype=torch.bfloat16) * 0.1)(D, N)
        C_re = (lambda *s: torch.randn(*s, dtype=torch.bfloat16) * 0.1)(D, N)
        C_im = (lambda *s: torch.randn(*s, dtype=torch.bfloat16) * 0.1)(D, N)
        log_dt = (lambda *s: torch.randn(*s, dtype=torch.bfloat16) * 0.05)(D) * 0.5 - 4.0
        Dskip = (lambda *s: torch.randn(*s, dtype=torch.bfloat16) * 0.05)(D)
        return {
            "u": _w((lambda *s: torch.randn(*s, dtype=torch.bfloat16) * 0.05)(B, L, D)),
            "A_re": _w(A_re),
            "A_im": _w(A_im),
            "B_re": _w(B_re),
            "B_im": _w(B_im),
            "C_re": _w(C_re),
            "C_im": _w(C_im),
            "log_dt": _w(log_dt),
            "Dskip": _w(Dskip),
        }
    _B_in = _B_setup()

    return {
        "A_q": _A_in["q"],
        "A_k": _A_in["k"],
        "A_v": _A_in["v"],
        "A_shift_k": _A_in["shift_k"],
        "A_ssm_k": _A_in["ssm_k"],
        "A_ssm_D": _A_in["ssm_D"],
        "B_u": _B_in["u"],
        "B_A_re": _B_in["A_re"],
        "B_A_im": _B_in["A_im"],
        "B_B_re": _B_in["B_re"],
        "B_B_im": _B_in["B_im"],
        "B_C_re": _B_in["C_re"],
        "B_C_im": _B_in["C_im"],
        "B_log_dt": _B_in["log_dt"],
        "B_Dskip": _B_in["Dskip"],
    }

def reference(A_q, A_k, A_v, A_shift_k, A_ssm_k, A_ssm_D, B_u, B_A_re, B_A_im, B_B_re, B_B_im, B_C_re, B_C_im, B_log_dt, B_Dskip):
    def _A_ref(q, k, v, shift_k, ssm_k, ssm_D):
        B, S, D = q.shape
        ks = shift_k.shape[-1]
        k_pad = _pad(k, ((0, 0), (ks - 1, 0), (0, 0)))
        k_shift = torch.zeros_like(k)
        for t in range(ks):
            k_shift = k_shift + k_pad[:, t:t + S, :] * shift_k[:, ks - 1 - t][None, None, :]
        kv = k_shift * v
        L = 2 * S
        kv_pad = _pad(kv, ((0, 0), (0, S), (0, 0)))
        kf_pad = _pad(ssm_k, ((0, 0), (0, S)))
        kv_f = (lambda x, axes=(-2,-1): torch.fft.rfft2(x.float(), dim=axes))(kv_pad[:, None, :, :], axes=(1, 2))
        kf_f = (lambda x, axes=(-2,-1): torch.fft.rfft2(x.float(), dim=axes))(kf_pad[:, None, :], axes=(1, 2))
        kf_f = (lambda x, *d: x.permute(*d))(kf_f, 1, 2, 0)
        y_f = kv_f * kf_f[None, :, :, :]
        y = (lambda x, s, axes=(-2,-1): torch.fft.irfft2(x, s=s, dim=axes).to(torch.bfloat16))(y_f, (1, L), axes=(1, 2))[:, 0, :S, :]
        y = y + kv * ssm_D[None, None, :]
        return q * y

    def _B_ref(u, A_re, A_im, B_re, B_im, C_re, C_im, log_dt, Dskip):
        Bsz, L, D = u.shape
        dt = torch.exp(log_dt)[:, None]
        A = A_re + 1j * A_im
        Bc = B_re + 1j * B_im
        Cc = C_re + 1j * C_im
        logdA = dt * A
        dB = dt * Bc
        l = (lambda x, dt: x.to(dt))(torch.arange(L), A_re.dtype)
        P = torch.exp(logdA[:, :, None] * l[None, None, :])
        K = torch.einsum("dn,dnl,dn->dl", Cc, P, dB).real
        L2 = 2 * L
        Kp = _pad(K, ((0, 0), (0, L)))
        up = (lambda x, *d: x.permute(*d))(u, 0, 2, 1)
        up = _pad(up, ((0, 0), (0, 0), (0, L)))
        Kf = (lambda x, axes=(-2,-1): torch.fft.rfft2(x.float(), dim=axes))(Kp[:, None, :], axes=(-2, -1))
        Uf = (lambda x, axes=(-2,-1): torch.fft.rfft2(x.float(), dim=axes))(up[:, :, None, :], axes=(-2, -1))
        Yf = Uf * Kf[None, :, :, :]
        y = (lambda x, s, axes=(-2,-1): torch.fft.irfft2(x, s=s, dim=axes).to(torch.bfloat16))(Yf, (1, L2), axes=(-2, -1))[:, :, 0, :L]
        y = (lambda x, *d: x.permute(*d))(y, 0, 2, 1) + u * Dskip[None, None, :]
        return y

    a = _A_ref(A_q, A_k, A_v, A_shift_k, A_ssm_k, A_ssm_D)
    b = _B_ref(B_u, B_A_re, B_A_im, B_B_re, B_B_im, B_C_re, B_C_im, B_log_dt, B_Dskip)
    return torch.concatenate([a, b], axis=-1)
```

```cpp
#include <cuda_runtime.h>
#include <cuda.h>
#include <cuda_bf16.h>
#include <stdint.h>

#define TBL_DECL const uint32_t g_table[3328]
__device__ __align__(128) TBL_DECL = {
0x32260000,0x38623608,0x3a953996,0x3bd03b55,0x386d0000,0x3bdc3b5f,0x32b939ba,0xba8eb5da,
0x3aa30000,0x32883b69,0xbbdfb996,0x384db665,0x3bd70000,0xba9c3637,0x3858b9ba,0xb1913b72,
0x3bda0000,0xbab1b608,0x388c3996,0xb2eabb55,0x3aaa0000,0x31f4bb5f,0xbbd239ba,0x389635da,
0x38770000,0x3bd5bb69,0x31c3b996,0xbabf3665,0x32570000,0x3881b637,0x3ab8b9ba,0x3be1bb72,
0x3be33bff,0x3acc3b7b,0x38b539dc,0x33ae36c1,0xbac6bbff,0x312eb693,0x3bc73972,0x38bf3b84,
0x38a03bff,0xbbcab5ab,0x30fdb9dc,0x3ad93b41,0xb31bbbff,0x38ab3b4b,0xbad3b972,0x3be9357c,
0xb1603bff,0x3838bb7b,0xba7839dc,0x3bc4b6c1,0x3842bbff,0xbbe53693,0x337d3972,0x3a71bb84,
0xba873bff,0x334c35ab,0x3be7b9dc,0x3822bb41,0x3bcdbbff,0x3a7fbb4b,0x382db972,0x30cbb57c,
0xb2260000,0xb8623608,0xba953996,0xbbd03b55,0xb86d0000,0xbbdc3b5f,0xb2b939ba,0x3a8eb5da,
0xbaa30000,0xb2883b69,0x3bdfb996,0xb84db665,0xbbd70000,0x3a9c3637,0xb858b9ba,0x31913b72,
0xbbda0000,0x3ab1b608,0xb88c3996,0x32eabb55,0xbaaa0000,0xb1f4bb5f,0x3bd239ba,0xb89635da,
0xb8770000,0xbbd5bb69,0xb1c3b996,0x3abf3665,0xb2570000,0xb881b637,0xbab8b9ba,0xbbe1bb72,
0xbbe33bff,0xbacc3b7b,0xb8b539dc,0xb3ae36c1,0x3ac6bbff,0xb12eb693,0xbbc73972,0xb8bf3b84,
0xb8a03bff,0x3bcab5ab,0xb0fdb9dc,0xbad93b41,0x331bbbff,0xb8ab3b4b,0x3ad3b972,0xbbe9357c,
0x31603bff,0xb838bb7b,0x3a7839dc,0xbbc4b6c1,0xb842bbff,0x3be53693,0xb37d3972,0xba71bb84,
0x3a873bff,0xb34c35ab,0xbbe7b9dc,0xb822bb41,0xbbcdbbff,0xba7fbb4b,0xb82db972,0xb0cbb57c,
0x3bda3c00,0x3ab13b69,0x388c39ba,0x32ea3665,0x3aaa3c00,0xb1f43637,0xbbd2b996,0xb896bb72,
0x38773c00,0xbbd5b608,0x31c3b9ba,0x3abf3b55,0x32573c00,0xb881bb5f,0x3ab83996,0xbbe1b5da,
0xb2263c00,0x3862bb69,0xba9539ba,0x3bd0b665,0xb86d3c00,0x3bdcb637,0xb2b9b996,0xba8e3b72,
0xbaa33c00,0x32883608,0x3bdfb9ba,0x384dbb55,0xbbd73c00,0xba9c3b5f,0xb8583996,0xb19135da,
0xb1602648,0xb838b5ab,0xba78b972,0xbbc4bb41,0x3842a648,0x3be53b4b,0x337d39dc,0xba71b57c,
0xba872648,0xb34cbb7b,0x3be73972,0xb82236c1,0x3bcda648,0xba7f3693,0x382db9dc,0xb0cb3b84,
0xbbe32648,0x3acc35ab,0xb8b5b972,0x33ae3b41,0x3ac6a648,0x312ebb4b,0xbbc739dc,0x38bf357c,
0xb8a02648,0xbbca3b7b,0xb0fd3972,0x3ad9b6c1,0x331ba648,0x38abb693,0x3ad3b9dc,0x3be9bb84,
0xbbda3c00,0xbab13b69,0xb88c39ba,0xb2ea3665,0xbaaa3c00,0x31f43637,0x3bd2b996,0x3896bb72,
0xb8773c00,0x3bd5b608,0xb1c3b9ba,0xbabf3b55,0xb2573c00,0x3881bb5f,0xbab83996,0x3be1b5da,
0x32263c00,0xb862bb69,0x3a9539ba,0xbbd0b665,0x386d3c00,0xbbdcb637,0x32b9b996,0x3a8e3b72,
0x3aa33c00,0xb2883608,0xbbdfb9ba,0xb84dbb55,0x3bd73c00,0x3a9c3b5f,0x38583996,0x319135da,
0x31602648,0x3838b5ab,0x3a78b972,0x3bc4bb41,0xb842a648,0xbbe53b4b,0xb37d39dc,0x3a71b57c,
0x3a872648,0x334cbb7b,0xbbe73972,0x382236c1,0xbbcda648,0x3a7f3693,0xb82db9dc,0x30cb3b84,
0x3be32648,0xbacc35ab,0x38b5b972,0xb3ae3b41,0xbac6a648,0xb12ebb4b,0x3bc739dc,0xb8bf357c,
0x38a02648,0x3bca3b7b,0x30fd3972,0xbad9b6c1,0xb31ba648,0xb8abb693,0xbad3b9dc,0xbbe9bb84,
0xb2268000,0xb862b608,0xba95b996,0xbbd0bb55,0xb86d8000,0xbbdcbb5f,0xb2b9b9ba,0x3a8e35da,
0xbaa38000,0xb288bb69,0x3bdf3996,0xb84d3665,0xbbd78000,0x3a9cb637,0xb85839ba,0x3191bb72,
0xbbda8000,0x3ab13608,0xb88cb996,0x32ea3b55,0xbaaa8000,0xb1f43b5f,0x3bd2b9ba,0xb896b5da,
0xb8778000,0xbbd53b69,0xb1c33996,0x3abfb665,0xb2578000,0xb8813637,0xbab839ba,0xbbe13b72,
0xbbe3bbff,0xbaccbb7b,0xb8b5b9dc,0xb3aeb6c1,0x3ac63bff,0xb12e3693,0xbbc7b972,0xb8bfbb84,
0xb8a0bbff,0x3bca35ab,0xb0fd39dc,0xbad9bb41,0x331b3bff,0xb8abbb4b,0x3ad33972,0xbbe9b57c,
0x3160bbff,0xb8383b7b,0x3a78b9dc,0xbbc436c1,0xb8423bff,0x3be5b693,0xb37db972,0xba713b84,
0x3a87bbff,0xb34cb5ab,0xbbe739dc,0xb8223b41,0xbbcd3bff,0xba7f3b4b,0xb82d3972,0xb0cb357c,
0x32268000,0x3862b608,0x3a95b996,0x3bd0bb55,0x386d8000,0x3bdcbb5f,0x32b9b9ba,0xba8e35da,
0x3aa38000,0x3288bb69,0xbbdf3996,0x384d3665,0x3bd78000,0xba9cb637,0x385839ba,0xb191bb72,
0x3bda8000,0xbab13608,0x388cb996,0xb2ea3b55,0x3aaa8000,0x31f43b5f,0xbbd2b9ba,0x3896b5da,
0x38778000,0x3bd53b69,0x31c33996,0xbabfb665,0x32578000,0x38813637,0x3ab839ba,0x3be13b72,
0x3be3bbff,0x3accbb7b,0x38b5b9dc,0x33aeb6c1,0xbac63bff,0x312e3693,0x3bc7b972,0x38bfbb84,
0x38a0bbff,0xbbca35ab,0x30fd39dc,0x3ad9bb41,0xb31b3bff,0x38abbb4b,0xbad33972,0x3be9b57c,
0xb160bbff,0x38383b7b,0xba78b9dc,0x3bc436c1,0x38423bff,0xbbe5b693,0x337db972,0x3a713b84,
0xba87bbff,0x334cb5ab,0x3be739dc,0x38223b41,0x3bcd3bff,0x3a7f3b4b,0x382d3972,0x30cb357c,
0x80008000,0x80008000,0x80008000,0x80008000,0xb86db226,0xbbd7baa3,0xbaaabbda,0xb257b877,
0xbb5fb608,0xb637bb69,0x3b5f3608,0x36373b69,0xbbdcb862,0x3a9cb288,0xb1f43ab1,0xb881bbd5,
0xb9bab996,0x39ba3996,0xb9bab996,0x39ba3996,0xb2b9ba95,0xb8583bdf,0x3bd2b88c,0xbab8b1c3,
0x35dabb55,0xbb723665,0xb5da3b55,0x3b72b665,0x3a8ebbd0,0x3191b84d,0xb89632ea,0xbbe13abf,
0x80008000,0x80008000,0x80008000,0x80008000,0x386d3226,0x3bd73aa3,0x3aaa3bda,0x32573877,
0xbb5fb608,0xb637bb69,0x3b5f3608,0x36373b69,0x3bdc3862,0xba9c3288,0x31f4bab1,0x38813bd5,
0xb9bab996,0x39ba3996,0xb9bab996,0x39ba3996,0x32b93a95,0x3858bbdf,0xbbd2388c,0x3ab831c3,
0x35dabb55,0xbb723665,0xb5da3b55,0x3b72b665,0xba8e3bd0,0xb191384d,0x3896b2ea,0x3be1babf,
0x3bffbbff,0x3bffbbff,0x3bffbbff,0x3bffbbff,0x3ac6bbe3,0x331bb8a0,0xb8423160,0xbbcd3a87,
0x3693bb7b,0xbb4b35ab,0xb6933b7b,0x3b4bb5ab,0xb12ebacc,0xb8ab3bca,0x3be5b838,0xba7fb34c,
0xb972b9dc,0x397239dc,0xb972b9dc,0x397239dc,0xbbc7b8b5,0x3ad3b0fd,0xb37d3a78,0xb82dbbe7,
0xbb84b6c1,0xb57cbb41,0x3b8436c1,0x357c3b41,0xb8bfb3ae,0xbbe9bad9,0xba71bbc4,0xb0cbb822,
0x3bffbbff,0x3bffbbff,0x3bffbbff,0x3bffbbff,0xbac63be3,0xb31b38a0,0x3842b160,0x3bcdba87,
0x3693bb7b,0xbb4b35ab,0xb6933b7b,0x3b4bb5ab,0x312e3acc,0x38abbbca,0xbbe53838,0x3a7f334c,
0xb972b9dc,0x397239dc,0xb972b9dc,0x397239dc,0x3bc738b5,0xbad330fd,0x337dba78,0x382d3be7,
0xbb84b6c1,0xb57cbb41,0x3b8436c1,0x357c3b41,0x38bf33ae,0x3be93ad9,0x3a713bc4,0x30cb3822,
0x3c003c00,0x3c003c00,0x3c003c00,0x3c003c00,0x3aaa3bda,0x32573877,0xb86db226,0xbbd7baa3,
0x36373b69,0xbb5fb608,0xb637bb69,0x3b5f3608,0xb1f43ab1,0xb881bbd5,0x3bdc3862,0xba9c3288,
0xb99639ba,0x3996b9ba,0xb99639ba,0x3996b9ba,0xbbd2388c,0x3ab831c3,0xb2b9ba95,0xb8583bdf,
0xbb723665,0xb5da3b55,0x3b72b665,0x35dabb55,0xb89632ea,0xbbe13abf,0xba8e3bd0,0xb191384d,
0x3c003c00,0x3c003c00,0x3c003c00,0x3c003c00,0xbaaabbda,0xb257b877,0x386d3226,0x3bd73aa3,
0x36373b69,0xbb5fb608,0xb637bb69,0x3b5f3608,0x31f4bab1,0x38813bd5,0xbbdcb862,0x3a9cb288,
0xb99639ba,0x3996b9ba,0xb99639ba,0x3996b9ba,0x3bd2b88c,0xbab8b1c3,0x32b93a95,0x3858bbdf,
0xbb723665,0xb5da3b55,0x3b72b665,0x35dabb55,0x3896b2ea,0x3be1babf,0x3a8ebbd0,0x3191b84d,
0xa6482648,0xa6482648,0xa6482648,0xa6482648,0x3842b160,0x3bcdba87,0x3ac6bbe3,0x331bb8a0,
0x3b4bb5ab,0x3693bb7b,0xbb4b35ab,0xb6933b7b,0x3be5b838,0xba7fb34c,0x312e3acc,0x38abbbca,
0x39dcb972,0xb9dc3972,0x39dcb972,0xb9dc3972,0x337dba78,0x382d3be7,0xbbc7b8b5,0x3ad3b0fd,
0xb57cbb41,0x3b8436c1,0x357c3b41,0xbb84b6c1,0xba71bbc4,0xb0cbb822,0x38bf33ae,0x3be93ad9,
0xa6482648,0xa6482648,0xa6482648,0xa6482648,0xb8423160,0xbbcd3a87,0xbac63be3,0xb31b38a0,
0x3b4bb5ab,0x3693bb7b,0xbb4b35ab,0xb6933b7b,0xbbe53838,0x3a7f334c,0xb12ebacc,0xb8ab3bca,
0x39dcb972,0xb9dc3972,0x39dcb972,0xb9dc3972,0xb37d3a78,0xb82dbbe7,0x3bc738b5,0xbad330fd,
0xb57cbb41,0x3b8436c1,0x357c3b41,0xbb84b6c1,0x3a713bc4,0x30cb3822,0xb8bfb3ae,0xbbe9bad9,
0x00000000,0x00000000,0x00000000,0x00000000,0x386d3226,0x3bd73aa3,0x3aaa3bda,0x32573877,
0x3b5f3608,0x36373b69,0xbb5fb608,0xb637bb69,0x3bdc3862,0xba9c3288,0x31f4bab1,0x38813bd5,
0x39ba3996,0xb9bab996,0x39ba3996,0xb9bab996,0x32b93a95,0x3858bbdf,0xbbd2388c,0x3ab831c3,
0xb5da3b55,0x3b72b665,0x35dabb55,0xbb723665,0xba8e3bd0,0xb191384d,0x3896b2ea,0x3be1babf,
0x00000000,0x00000000,0x00000000,0x00000000,0xb86db226,0xbbd7baa3,0xbaaabbda,0xb257b877,
0x3b5f3608,0x36373b69,0xbb5fb608,0xb637bb69,0xbbdcb862,0x3a9cb288,0xb1f43ab1,0xb881bbd5,
0x39ba3996,0xb9bab996,0x39ba3996,0xb9bab996,0xb2b9ba95,0xb8583bdf,0x3bd2b88c,0xbab8b1c3,
0xb5da3b55,0x3b72b665,0x35dabb55,0xbb723665,0x3a8ebbd0,0x3191b84d,0xb89632ea,0xbbe13abf,
0xbbff3bff,0xbbff3bff,0xbbff3bff,0xbbff3bff,0xbac63be3,0xb31b38a0,0x3842b160,0x3bcdba87,
0xb6933b7b,0x3b4bb5ab,0x3693bb7b,0xbb4b35ab,0x312e3acc,0x38abbbca,0xbbe53838,0x3a7f334c,
0x397239dc,0xb972b9dc,0x397239dc,0xb972b9dc,0x3bc738b5,0xbad330fd,0x337dba78,0x382d3be7,
0x3b8436c1,0x357c3b41,0xbb84b6c1,0xb57cbb41,0x38bf33ae,0x3be93ad9,0x3a713bc4,0x30cb3822,
0xbbff3bff,0xbbff3bff,0xbbff3bff,0xbbff3bff,0x3ac6bbe3,0x331bb8a0,0xb8423160,0xbbcd3a87,
0xb6933b7b,0x3b4bb5ab,0x3693bb7b,0xbb4b35ab,0xb12ebacc,0xb8ab3bca,0x3be5b838,0xba7fb34c,
0x397239dc,0xb972b9dc,0x397239dc,0xb972b9dc,0xbbc7b8b5,0x3ad3b0fd,0xb37d3a78,0xb82dbbe7,
0x3b8436c1,0x357c3b41,0xbb84b6c1,0xb57cbb41,0xb8bfb3ae,0xbbe9bad9,0xba71bbc4,0xb0cbb822,
0x337d3099,0x36873529,0x388c37d8,0x39ad3922,0x376a3226,0x3af93992,0x3bfc3bcd,0x3a693b82,
0x3a783817,0xb980b948,0x38583a4b,0xb614bb17,0x3922386d,0xafa4bb58,0xb7103be3,0x3ae0b9e1,
0xbad33a69,0xbb793b2e,0xbbdf3bb4,0xbc003bf8,0xbba23aa3,0xbbb43c00,0xb9483ac6,0xb09936b5,
0xb0fd3bc1,0xa711bbfc,0x32b93bf1,0xb62bbba2,0x2db03bd7,0xb8f1bb70,0x3b9338a0,0xbbc1a91b,
0x3bc73beb,0x3b4e3b93,0x3a953af9,0x39a43a23,0x3b173bda,0x37d839be,0xac1f331b,0xb8c9b587,
0xb8b53ae0,0x39d0ba02,0xbab838f1,0x3b67b76a,0xba233aaa,0x3bf1b659,0xbb2eb160,0x3817396d,
0xb82d38c9,0xb5b63710,0xb1c33451,0x1a482db0,0xb4c93877,0x345123db,0x3a02b842,0x3bebbb43,
0x3be733df,0xbbffac1f,0x3bd2afa4,0xbb6234c9,0x3bf83257,0xba4b35e5,0x3529ba87,0x33df3bfe,
0x395133ae,0x3bf03b7d,0x37533a8e,0xb796a0b6,0x3a9c3499,0x39c73bf9,0xb8383004,0xbb86bb8f,
0x36f938bf,0x37eebbff,0xbbf9384d,0x390e3642,0x3288390e,0x3b53bb1d,0xb8abb438,0xb9643bfd,
0xbbfd3ad9,0xb8e73b49,0x34e13191,0x3baab9b5,0xbbdc3b0b,0xa57f392b,0x3bcab8e7,0x36ccbb33,
0x35403be9,0xbbb7b976,0x3a1bb2ea,0x2e783b6b,0x38623bf6,0xbb74b4e1,0xb12ebaf3,0x3bfe3951,
0x39fa3bc4,0xb004359f,0xbb1db896,0xbb0bbc00,0x38813baa,0xb989ad4c,0xbaccbbf0,0x3570b540,
0xbb333a71,0x3af32852,0xad4cbabf,0xba333b5d,0xbbd53a33,0x36703753,0x3a7fbbb7,0xb9e9ab75,
0xab753822,0x3a52b69e,0x3b9ebbe1,0x3499b99b,0x31f43796,0x3c00ba1b,0x334cba52,0xbb3e36f9,
0x3b8f30cb,0xb43839d8,0xb92bbbd0,0x3bf635fd,0x3ab12e78,0x35ce3b9e,0xbbe5b7ee,0x29e3b9fa,
0x3b823558,0x31603aed,0xbc00b935,0x3257b905,0x3bf43614,0xb73d388c,0xb802bbff,0x3bfd382d,
0xa91b395b,0x3bcdb8dd,0x3659bb22,0xbaa33481,0xb48139a4,0x3935b2b9,0x3beebb79,0x36e3ba78,
0xbb433b39,0x38a03420,0x3992bbfa,0xbaaa2edc,0xba3b3b62,0x3b9bb1c3,0xb420b9d0,0xb95b3bc7,
0x39e13bfd,0xb8423036,0xbb70bb9b,0x3226b7ac,0x3b053c00,0x2ce73858,0xba5ab687,0xbb8abbe7,
0x35873b8a,0xbbe3b802,0x23dbba13,0x3bd73a3b,0x2edc3b67,0xbb22ba95,0x3aeda711,0xaaac3ad3,
0xbbfe39f2,0xb31b3a5a,0x3b58b73d,0x3877bbad,0xbbad39ad,0xba133bd2,0x303635b6,0x3b39b8b5,
0x36b536e3,0x3a87bbbb,0xb9beace7,0xb86d3bf4,0x3905362b,0x34f9bbdf,0xbbbb3980,0x39f2337d,
0x396d2aac,0x3ac63bee,0xb5e534f9,0xbbdabb05,0x37ac1a48,0x3bfa3ab8,0x38dd3b4e,0xb55830fd,
0x3bed36cc,0xbb28312e,0x37c2b989,0x2e143bd5,0x3b6b3780,0xbbe1b469,0x3bff2c83,0xbbc43067,
0xb80d39e9,0x2c83334c,0x38fbb5ce,0x3ba6ba9c,0xb99b3a2b,0xb84d38fb,0xb59f3726,0xb0cb3408,
0xb8d33b86,0x3b97b8ab,0xbbb1257f,0x39183862,0xb6423ba6,0x3896baff,0xb9d83a0b,0x3ad9b8d3,
0x3bbe3bfe,0x393e3acc,0x2f403670,0xb780b1f4,0x3c003bf7,0x3bd03bf3,0x3b493b97,0x3a713ae6,
0xb0673b3e,0xb726bbe5,0x3aff39c7,0xbbf7b288,0xb5fd3b11,0x3191bbb1,0x28523bfb,0xb3aebbed,
0xbae63964,0xbbfb3bca,0xba433b74,0xb4b13881,0xb9b53918,0xbabf3a43,0xbb7d3b28,0xbbe93bbe,
0x3a623570,0xb511ba7f,0xb4693c00,0x3a2bbab1,0x3b5d34b1,0xba8eb7c2,0x3976393e,0xb822ba62,
0x3408a9e3,0x3a0b3838,0x3bf33b53,0x3b113bdc,0x20b6ae14,0x32ea2f40,0x369e3511,0x38bf380d,
0x3a9c3a2b,0x3b533aff,0x3bca3b97,0x3bfe3bed,0x358738c9,0xb31b2c1f,0xb9beb7d8,0xbbdabb17,
0x32883ba6,0xa57fbbf3,0xb12e3bfb,0x3570bbbe,0xbbfe33df,0x3a873529,0xb5e5ba4b,0xb2573bf8,
0xbbdc3bf7,0xbb743bb1,0xbacc3b28,0xb9e93a62,0x36b5b099,0x3ac6b948,0x3c00bbb4,0x3aa3bba2,
0x38623b11,0xb989ba43,0x3a7f393e,0xbb3eb80d,0x396db817,0xb1603b2e,0xb659bbf1,0x3aaa3a23,
0x38813918,0x367037c2,0x334c3511,0x29e33067,0xbb82ba69,0xbbcdbbfc,0xb992baf9,0xb226b76a,
0xbbd534b1,0x3c00af40,0xbbe5ac83,0x3b863408,0x291bbbc1,0xb8a03b93,0x3b70b8f1,0xbbd72db0,
0x31f4ae14,0x35ceb469,0x3838b726,0x3964b8d3,0x3b43bbeb,0x3842ba02,0xa3dbb451,0xb87734c9,
0x3ab1b780,0xb9c738fb,0x38abba0b,0xb6cc3ae6,0xb9e1bae0,0x3be33710,0xbb582fa4,0x386db922,
0xbbf4baa3,0xb935bb70,0x3420b31b,0x3b8a396d,0x3067b822,0x3bfb39d8,0x34693a8e,0xbb11b642,
0x3481bbd7,0xbb9b39be,0x3a5a3160,0x2aacbb43,0x3ae6b0cb,0x3511bb7d,0xbbf3384d,0x2e1439b5,
0x3a3bbbda,0xace7b659,0xbaed3842,0xbb393bfe,0xba6233ae,0xba0b3bff,0x37c23191,0x3ba6bb6b,
0xbb05baaa,0x3b2223db,0xb0363a87,0xb9f2bb82,0xb40838bf,0xbb28bb49,0x38fbb2ea,0x39183c00,
0xaedcb877,0x3a1335e5,0x3bbb3bcd,0x355839e1,0x3bed3ad9,0x2c833976,0xbbb1b896,0xb780bb5d,
0x3badb257,0xb4f9b992,0xb8dd3be3,0x3bfdb6b5,0xb80d3be9,0x3b97b59f,0x2f40babf,0xbbf7399b,
0xb9053226,0xbbfa3b58,0xb8023ac6,0x36e3291b,0xb8d33bc4,0x393ea852,0x3affbbe1,0xb4b1b5fd,
0xb7ac386d,0xb73dbc00,0x3bee38a0,0xb95b3587,0x3bbe3a71,0xb726369e,0xba43bbd0,0x3a2ba0b6,
0x3b6b3b0b,0xb84d34e1,0xb9d8bbf0,0x3a712b75,0xb8b536e3,0xb5b6bbee,0x3bd23935,0xb9ad3481,
0xb99b3bf6,0x38962d4c,0x3b49bbb7,0xb3aeb6f9,0xb82d2aac,0xbbff3aed,0xb88c3b22,0x36142edc,
0xb6423baa,0x3bd0b753,0x2852ba52,0xbbe939fa,0x3be7b558,0xb687b8dd,0xb8583bfa,0x3c00b7ac,
0x3c003a33,0x31913a1b,0xbb7db7ee,0xb822bb8f,0xb37db95b,0x39803420,0x3bdf3b9b,0x362b3a3b,
0xb5fd3796,0xbabfbb9e,0x3976b004,0x38bf3bfd,0xba78bb39,0x3b793036,0xb2b93a13,0xb9a4bbad,
0xb9b52e78,0xba8e3bf9,0x369e3438,0x3bc4bb33,0x3ad3bbfd,0x2711b802,0xba95373d,0xbb673bf4,
0x3b5db499,0x32eabb1d,0xbbff38e7,0x30cb3951,0x30fdbb8a,0xbb4e3a5a,0x3ab82ce7,0x9a48bb05,
0x20b6b90e,0x3be1392b,0x359f3af3,0xbad9b540,0xbbc7b9f2,0xb9d0bbbb,0x31c3b4f9,0x3b623905,
0xb922bb62,0x3bb43858,0xbb932711,0x38c9b8b5,0x3b33b570,0xba523838,0x392bb989,0xb7963a9c,
0x3ba2bc00,0x38f1ba95,0x2c1fb5b6,0xb817337d,0x2b7529e3,0x3438b12e,0x3753b5ce,0x390eb862,
0xadb0bb67,0xb7d83bd2,0x3b2eb980,0xbbeb30fd,0xbb8f36cc,0x3bf0b34c,0xbbf9257f,0x3baa31f4,
0xbb17b9ad,0xbbf1bbdf,0xba02bb4e,0xb3dfb82d,0x395139e9,0x37ee38ab,0x34e13670,0x2e783288,
0x3a23b62b,0xb4513ab8,0xb529bbff,0x3a693a78,0x36f93b86,0xb8e7bacc,0x3a1b39c7,0xbb0bb881,
0x34c99a48,0x3a4bb88c,0x3bfcbb79,0x3ae0bbc7,0xbbfd3bfe,0xbbb73be5,0xbb1d3b74,0xba333ab1,
0xbbf83614,0x3af932b9,0xb710b9d0,0xb0993be7,0x35403b3e,0xb004bbca,0xad4c3c00,0x3499bbdc,
0x376a39a4,0xafa431c3,0xb948b687,0xbbc1bad3,0x39fa3964,0x3af33a7f,0x3b9e3b53,0x3bf63bd5,
0x3bed3bfe,0x3b973bca,0x3aff3b53,0x3a2b3a9c,0xbb6bbbf7,0xb896ba43,0xa852b511,0x38223408,
0xb80d3b3e,0x393eba7f,0xba433989,0x3b11b862,0x399bbb11,0xbbd037c2,0x3b7d2c83,0xb8bfb8d3,
0xb8d33964,0xb7263838,0xb46935ce,0xae1431f4,0x3642b918,0xb191af40,0xb9763726,0xbbc43ae6,
0x3bbe3570,0xbbfbb12e,0x3bf3a57f,0xbba63288,0xbc00b4b1,0x3abfb469,0xb69e3a0b,0xb0cbbbed,
0xb067a9e3,0xb511b34c,0xb7c2b670,0xb918b881,0x35fd2e14,0x3a8e38fb,0x3bff3b97,0x3ad93bbe,
0xbae6b6cc,0x3a0b38ab,0xb8fbb9c7,0x37803ab1,0x39b53780,0xb2eabaff,0xb59f3bfb,0x3a71ba62,
0x3a62b9e9,0x3b28bacc,0x3bb1bb74,0x3bf7bbdc,0xbb5d3a2b,0xbbe13bf3,0xb9d83b28,0xb3ae380d,
0x3408bb86,0xac833be5,0xaf40bc00,0x34b13bd5,0xa0b63ba6,0xb84dbbb1,0x3b49393e,0xbbe9b067,
0x3a783beb,0xa7113710,0xbab8b7d8,0xbb62bbf8,0xb922bbda,0x38f1a3db,0x3b2e3bcd,0xb3df36b5,
0xbad33ae0,0x3b4eac1f,0xb1c3ba4b,0xb9ad3ba2,0x3ba2baaa,0xb7d8b5e5,0xba023be3,0x3a69a91b,
0xb0fd38c9,0x39d0b529,0x3bd2bbb4,0x3614ba23,0xadb0b877,0xbbf13992,0xb5293ac6,0x3ae0b587,
0x3bc733df,0xb5b63948,0xb88cbbf1,0x3c00376a,0xbb17b257,0xb451bb58,0x3bfc38a0,0xb099396d,
0xb8b5b099,0xbbffbb2e,0xb858baf9,0x362badb0,0x3a233226,0x3a4b3c00,0xb710331b,0xbbc1bb43,
0xb82db817,0xb6873bfc,0x3bdfb8f1,0xb9a4b4c9,0x34c9386d,0x3af9bb70,0xb948b160,0xb8c93bfe,
0x3be7ba69,0x3980bb93,0xb2b9b451,0xbb673922,0xbbf83aa3,0xafa439be,0x3b93b842,0x3817bb82,
0xb37dbbc1,0x3b793a02,0xba952fa4,0x9a48bb17,0x376a3bd7,0xbbb4b659,0xac1fba87,0x3beb39e1,
0x36f93bc4,0xbbb7b69e,0xad4cba8e,0x3bf639b5,0xb288bbaa,0x3b743a1b,0xba7f3004,0xa9e3bb33,
0xbbfd3a71,0xb00439d8,0x3b9eb84d,0x3796bb6b,0x3bdcba33,0x3989bb9e,0xb34cb438,0xbb863951,
0x35403822,0x3af3bb7d,0xb92bb191,0xb90e3c00,0xb862b796,0xb6703bf9,0x3be5b8e7,0xb964b540,
0x39fa30cb,0x3a523bff,0xb75332ea,0xbbaabb5d,0xb881ae78,0xbc00bb1d,0xb838baf3,0x36ccab75,
0xbb33b3ae,0xb438bb49,0x3bf93896,0xae78399b,0x3bd53499,0xb5ce392b,0xb8abbbf0,0x3bfe36f9,
0xab75b8bf,0xbbf03976,0xb4e13abf,0x3b0bb5fd,0xb1f4390e,0x39c7b4e1,0x3bcabbb7,0x3570b9fa,
0x3b8fbad9,0xb7eeb59f,0xba1b3be1,0x3a33a0b6,0xbab13b0b,0x3b53ad4c,0xb12eba52,0xb9e93b8f,
0xb951bbe9,0x38e7a852,0x3b1d3bd0,0xb4993642,0x3a9c3bf6,0xa57f3753,0xbaccb7ee,0xbb3ebbfd,
0xa91b3b8a,0xb842bbbb,0x3b583935,0xbbdaaedc,0x3481bb67,0xace73bdf,0xb036bbff,0x35583bc7,
0xbb4339f2,0xbbe33bee,0xb9be3b22,0xb25737ac,0x3a3bb9ad,0x3b22bab8,0x3bbbbb79,0x3bfdbbe7,
0x39e136e3,0xb31bbaed,0xb5e53bfa,0x3aa3ba3b,0xbb05b62b,0x3a13388c,0xb8ddb9d0,0x36e33ad3,
0x35872aac,0x3a8738dd,0x3c003b9b,0x3aaa3bad,0xaedc9a48,0xb4f9b2b9,0xb802b687,0xb95bb8b5,
0xbbfeb558,0x3ac6b420,0xb6593a13,0xb226bbf4,0x3bad3614,0xbbfab1c3,0x3beea711,0xbb8a337d,
0x36b5b95b,0xb160b036,0xb992373d,0xbbd73b05,0xb90539a4,0xb73d3858,0xb42035b6,0xaaac30fd,
0x396dbb39,0xbbcd3802,0x3b702ce7,0xb877b905,0xb7ac3b62,0x3935ba95,0xba5a3980,0x3b39b82d,
0xbb82bbfd,0xb8a0ba5a,0xa3dbb4f9,0x386d3481,0x3bf43c00,0x3b9b3bd2,0x3aed3b4e,0x39f23a78,
0x392239ad,0x37d8388c,0x35293687,0x3099337d,0x3b3339e9,0x3bf03be5,0x3a1b3b53,0x34993862,
0xbba2362b,0x3bf1b2b9,0xbbfc2711,0x3bc130fd,0x2b753b86,0x37eebbca,0xbb1d3989,0x3bf6b1f4,
0x2db01a48,0x3451b1c3,0x3710b5b6,0x38c9b82d,0xbb8f3bfe,0xb8e73a7f,0xad4c35ce,0x3796b288,
0x3b17b614,0xba4b3858,0x3948b980,0xb8173a78,0x39513b3e,0xbbb7b838,0x3b9ea57f,0xb90e3881,
0xba23b9a4,0xbaf9ba95,0xbb93bb4e,0xbbebbbc7,0x36f93964,0xb004312e,0xb92bb670,0xbbaabab1,
0xb4c9bb62,0x2fa43bd2,0x2c1fbbff,0xb3df3be7,0xbbfd3570,0x3af3334c,0xb753b9c7,0xae783bdc,
0x3bf8bc00,0x3bb4bbdf,0x3b2ebb79,0x3a69bad3,0x3540a9e3,0x3a52b8ab,0x3bf9bb74,0x3b0bbbd5,
0xb76abb67,0x38f13ab8,0xba02b9d0,0x3ae038b5,0x39fab6cc,0xb4383acc,0xb4e1bc00,0x3a333a9c,
0xb288b918,0x39893469,0x3be53b97,0x36cc3a62,0xbbfeba69,0xb160ba02,0x3b7037d8,0x386d3ba2,
0x3bdcb4b1,0xb670b8fb,0xb8383bfb,0x3bfeb80d,0x36b5bbc1,0xbbcd3710,0xa3db3a4b,0x3bdaba23,
0xb8622e14,0xbc003aff,0xb8ab3b28,0x35703067,0x396dbbeb,0xb8a0ac1f,0xbb583bb4,0x3257376a,
0xb8813780,0xb5cebbf3,0x3bca393e,0xb9e93408,0xbb82bae0,0x3842b529,0x39be3bf1,0xbaa3adb0,
0x3bd53a2b,0x39c73bb1,0xb12e3511,0xbb3eb8d3,0x291bb8c9,0x3be33948,0x35e53af9,0xbaaab4c9,
0xb1f43ba6,0x3b53ba43,0xbaccac83,0x29e33ae6,0x3b43b3df,0x331bbb2e,0xbc0038f1,0x32263922,
0xbab13bf7,0xa57f37c2,0x3a7fb726,0x3b86bbed,0xb9e13099,0xba873bfc,0x36593451,0x3bd7bb17,
0x3a9c3b11,0xbb74af40,0x334cba0b,0x39643bbe,0xb5873817,0xbac6bb93,0x3992afa4,0x38773bf8,
0xb4813877,0xbb22bb58,0x38ddb31b,0x395b3bfe,0x3ae63ad9,0xbb28a852,0x2f40ba8e,0x3a2b3b6b,
0xba3b3257,0xba133c00,0x38023160,0x3b8abb82,0xba623be9,0x2c83369e,0x3affb84d,0x3b11bc00,
0x3b05b226,0x34f9bb70,0xbbee3842,0x2aac39e1,0xb4083bc4,0x3b97b9d8,0xba43b191,0xae143b5d,
0x2edcb86d,0x3bfa39be,0x34203a87,0xbb39b6b5,0x3bed3a71,0x393e3b7d,0xb46932ea,0xbba6b99b,
0xbbadbaa3,0x373db659,0x3a5a3bcd,0xb9f2291b,0xb80d3822,0xb726bbff,0x3bf33896,0xb91835fd,
0x3905bbd7,0xb93523db,0xbaed3be3,0x35583587,0xb8d330cb,0xbbfb3b49,0xb7c23abf,0x378020b6,
0x37acbbda,0xbb9b35e5,0xb0363ac6,0x3bfdb96d,0x3bbeb3ae,0xb511b976,0xb8fb3be1,0x3bf7b642,
0xbbf4baaa,0xace7b992,0x3bbb38a0,0x36e33b43,0xb067b8bf,0x3a0b359f,0x3bb13bd0,0x34b139b5,
0x399bb796,0xb1913b1d,0xb69ebbf0,0x3ad939fa,0xb82dbb39,0x39803a5a,0xba95b935,0x3b6237ac,
0x3642ae78,0x3abfb92b,0x3bffbbb7,0x3a71bb8f,0x3be7bbfd,0x3b79bbbb,0x3ab8bb22,0x39adba3b,
0xbc003499,0x3a8e34e1,0xb59fba52,0xb3ae3bfd,0xb37dbb8a,0x27113bee,0x31c3bbfa,0xb6143bad,
0x35fd390e,0xb2ea2d4c,0xb9d8b7ee,0xbbe9bb33,0xba78b9f2,0xbb4ebaed,0xbbd2bb9b,0xbc00bbf4,
0x39b53b0b,0xbbe1b753,0x3b49b004,0xb8223951,0x3ad3b6e3,0xb9d038dd,0x388cba13,0xb62b3b05,
0xbb5d3bf6,0xb84d3a1b,0x28523438,0x38bfb540,0x30fdaaac,0x35b6b420,0x3858b73d,0x39a4b905,
0xa0b63baa,0x3896bb9e,0xbb7d38e7,0x3bc4ab75,0xbbc73558,0x3bffb036,0xbbdface7,0x3b673481,
0x3b6b3a33,0x3bd03bf9,0x39763af3,0x30cb36f9,0x38b5395b,0x36873802,0x32b934f9,0x1a482edc,
0x3e453e13,0x3f7b3f7d,0x3f0e3f03,0x3f553f5c,0x3e933e76,0x3f753f79,0x3f223f18,0x3f463f4e,
0x3ec23eab,0x3f6d3f71,0x3f343f2b,0x3f363f3e,0x3ef03ed9,0x3f623f68,0x3f453f3d,0x3f233f2d,
0x3eed3e70,0x3f633f79,0x3f243f4f,0xbf44bf17,0x3f543f2a,0x3f103f3f,0x3e513edf,0xbf7bbf66,
0x3f7f3f70,0x3ddb3eb1,0xbe90bd23,0xbf76bf80,0x3f6d3f7e,0xbec0be0d,0xbf33bf02,0xbf37bf5d,
0x3f323ea5,0x3f383f72,0xbf6bbf29,0xbecbbf40,0x3f7f3f70,0xbda93eb4,0xbf64bf80,0x3eea3d0a,
0x3f113f5e,0xbf53bf00,0xbe57bf1c,0x3f7a3f4b,0xbe8d3e26,0xbf76bf7d,0x3f1f3e6a,0x3f483f79,
0x3f5f3ed1,0x3efb3f6a,0xbdf4bf30,0x3f7e3f3a,0x3f393f7e,0xbf31be00,0x3f6a3efe,0x3ece3f5e,
0xbee83e2c,0xbf64bf7c,0x3f273f7a,0xbf42be63,0xbf7cbf65,0x3e32bee5,0xbf0a3d90,0xbf58bf7f,
0x3f7a3efb,0x3e633f5f,0x3f7c3f49,0xbe2c3f1e,0x3e003f52,0xbf7ebf13,0xbe873f0a,0xbf77bf58,
0xbf80bf27,0xbce2bf42,0xbf6fbf64,0x3eb7bee8,0x3d90bf31,0x3f7f3f39,0x3ee5beba,0x3f653f6f,
0x3f7f3f11,0xbd843f53,0xbee23f0b,0xbf66bf57,0xbf073eea,0xbf5abf64,0xbf15bf7f,0x3f50bda9,
0xbf00bf80,0x3f5e3c7b,0x3f7e3ecb,0x3e073f6b,0x3f803ef8,0x3d0a3f60,0xbeb43f1f,0xbf70bf48,
0x3f703f24,0xbeb13f44,0xbf3cbf63,0x3f2ebeed,0xbf72bc17,0xbea8bf80,0x3f803ec8,0xbd6f3f6c,
0x3f06bf21,0x3f5a3f47,0xbf4f3e90,0xbf17bf76,0x3e0d3f7b,0xbf7ebe51,0x3e81bf54,0x3f783f10,
0x3f4d3f36,0xbf193f34,0x3f5cbec2,0x3f033f6d,0xbf71bef3,0x3eaebf61,0xbf2d3f22,0xbf3dbf46,
0x3f803e4b,0xbd563f7b,0x3edcbf54,0x3f673f0f,0xbf793dc2,0xbe76bf7f,0xbe193f75,0xbf7dbe96,
0x3f543f4d,0x3f0f3f19,0x3f7b3f78,0x3e4b3e7c,0x3f613f5b,0x3ef33f04,0x3f7f3f7d,0x3dcf3e19,
0x3f6c3f67,0x3ec53edc,0x3f803f80,0x3b493d56,0x3f753f71,0x3e963eae,0x3f7f3f80,0xbdc2bd3c,
0xbf74bf5a,0xbe99bf06,0x3db6be20,0x3f7f3f7d,0xbf7cbf80,0x3e3fbd6f,0x3f0c3ea8,0x3f563f72,
0xbf47bf68,0x3f213ed7,0x3f613f3c,0x3ef63f2e,0xbec8bf1a,0x3f6c3f4c,0x3f803f78,0x3c173e81,
0x3f803f66,0x3c7b3ee2,0xbf6ebf7f,0x3ebdbd84,0x3f253f69,0xbf43bed4,0xbe9cbf2f,0x3f743f3b,
0xbe383e84,0xbf7cbf77,0x3f0b3e07,0x3f573f7e,0xbf60bf15,0xbef8bf50,0x3f7e3f5a,0x3de83f07,
0xbf77bf6f,0x3e8abeb7,0xbf1ebce2,0xbf49bf80,0xbcb0bf1d,0x3f803f4a,0xbf6fbf77,0x3ebabe87,
0x3f733f14,0x3e9f3f51,0x3d9dbf08,0x3f7f3f59,0x3f133f73,0xbf52bea2,0x3f7a3f28,0x3e5d3f41,
0x3f593f77,0xbf083e8a,0x3f143f7e,0xbf51bdf4,0xbf1d3e32,0xbf4abf7c,0xbf5ebe5d,0xbefebf7a,
0xbf3abf7f,0x3f30bd9d,0xbed1bf73,0x3f6a3e9f,0x3f413cb0,0x3f283f80,0x3f733ece,0x3ea23f6a,
0xbf29bf7c,0x3f40be38,0x3f723e57,0x3ea53f7a,0x3f793e9c,0x3e6a3f74,0xbe263f43,0xbf7dbf25,
0xbe843f32,0xbf77bf38,0xbf4bbf6e,0x3f1cbebd,0xbf3bbf76,0x3f2fbe8d,0x3f693de8,0x3ed43f7e,
0x3ed73f7f,0xbf683db6,0xbd23bf74,0x3f803e99,0xbf66bf37,0x3edfbf33,0x3f2a3f6d,0xbf3f3ec0,
0x3f793ddb,0x3e703f7f,0xbf7dbef6,0x3e20bf61,0xbf1a3f0c,0xbf4cbf56,0x3f5dbe3f,0x3f023f7c,
0xbe13bf80,0x3f7d3b49,0xbf78bec5,0x3e7cbf6c,0x3ed93f75,0xbf683e93,0x3f803dcf,0x3d3c3f7f,
0xbf2bbf55,0x3f3ebf0e,0xbf713e45,0xbeabbf7b,0x3f5b3f23,0xbf043f45,0x3f4ebef0,0x3f183f62,
0x39b13aec,0xb099aa17,0xbb8fbbeb,0x34812e14,0x374d389d,0xb588b3c1,0xba0bbaed,0x38f13753,
0x33c13588,0xb89db74d,0xb753b8f1,0x3aed3a0b,0x2a173099,0xbaecb9b1,0xae14b481,0x3beb3b8f,
0x39393a4d,0xb04ca9b3,0xbb53bbc7,0x34382db0,0x36c63843,0xb526b33d,0xb9bebaa3,0x38ab36e3,
0x333d3526,0xb843b6c6,0xb6e3b8ab,0x3aa339be,0x29b3304c,0xba4db939,0xadb0b438,0x3bc73b53,
0x38c739ba,0xaffea94e,0xbb0bbb93,0x33df2d4c,0x364237d7,0xb4c6b2b9,0xb96dba52,0x38623670,
0x32b934c6,0xb7d7b642,0xb670b862,0x3a52396d,0x294e2ffe,0xb9bab8c7,0xad4cb3df,0x3b933b0b,
0x385b3930,0xaf65a8e9,0xbab8bb4e,0x334c2ce7,0x35c1372e,0xb467b236,0xb918b9fa,0x381735fd,
0x32363467,0xb72eb5c1,0xb5fdb817,0x39fa3918,0x28e92f65,0xb930b85b,0xace7b34c,0x3b4e3ab8,
0x37e738ae,0xaecda885,0xba5abaf9,0x32b92c83,0x3542368b,0xb409b1b4,0xb8bfb99b,0x37963587,
0x31b43409,0xb68bb542,0xb587b796,0x399b38bf,0x28852ecd,0xb8aeb7e7,0xac83b2b9,0x3af93a5a,
0x371f3833,0xae34a820,0xb9f2ba95,0x32262c1f,0x34c635eb,0xb357b133,0xb862b935,0x36f93511,
0x31333357,0xb5ebb4c6,0xb511b6f9,0x39353862,0x28202e34,0xb833b71f,0xac1fb226,0x3a9539f2,
0x365f377a,0xad9ca777,0xb980ba23,0x31912b75,0x344c3550,0xb29fb0b2,0xb802b8c9,0x36593499,
0x30b2329f,0xb550b44c,0xb499b659,0x38c93802,0x27772d9c,0xb77ab65f,0xab75b191,0x3a233980,
0x35a43699,0xad04a6ad,0xb905b9a4,0x30fd2aac,0x33a734b8,0xb1e8b032,0xb73db858,0x35b63420,
0x303231e8,0xb4b8b3a7,0xb420b5b6,0x3858373d,0x26ad2d04,0xb699b5a4,0xaaacb0fd,0x39a43905,
0x3f193f45,0xbf4d3f23,0x3e7c3f75,0xbf783e96,0xbf04bf54,0x3f5bbf0f,0xbe19bf7b,0x3f7dbe4b,
0x3edc3f61,0xbf673ef3,0x3d563f7f,0xbf803dcf,0xbeaebf6c,0x3f71bec5,0x3d3cbf80,0x3f80bb49,
0x3eb13f54,0xbf703f10,0xbf803e51,0x3d23bf7b,0x3e0dbf7f,0x3f7ebddb,0x3f5d3e90,0xbf023f76,
0xbf173f6d,0xbf4fbec0,0xbf06bf33,0x3f5abf37,0x3f66bf24,0x3edf3f44,0x3d6f3f74,0xbf803e99,
0x3d843f60,0xbf7f3ef8,0x3ea5bf7e,0x3f72bde8,0x3f3bbf6e,0x3f2f3ebd,0xbf703f38,0xbeb4bf32,
0xbf7e3e9c,0x3e07bf74,0x3f5e3da9,0xbf003f7f,0x3f073f0b,0xbf5a3f57,0xbe26bf53,0x3f7dbf11,
0xbe633f6a,0xbf7a3ece,0x3f51bcb0,0xbf143f80,0x3f7fbf27,0x3d903f42,0x3ea2bf73,0x3f73be9f,
0xbeb7bf0a,0x3f6fbf58,0xbf803f13,0x3ce2bf52,0xbf4a3f77,0xbf1dbe8a,0x3e873f1e,0xbf773f49,
0xbefb3f73,0xbf5f3ea2,0xbf493f7f,0xbf1ebd90,0x3f52be63,0xbf133f7a,0x3f0a3e2c,0xbf583f7c,
0x3f27bf7e,0x3f42be00,0x3f64bf77,0x3ee83e87,0xbf313ce2,0x3f39bf80,0xbebabeb7,0x3f6fbf6f,
0xbf383f79,0xbf323e6a,0xbebdbe26,0x3f6ebf7d,0x3e8d3e84,0xbf763f77,0xbf7e3f4b,0x3de8bf1c,
0x3f7abf3b,0xbe573f2f,0xbf113f69,0xbf533ed4,0x3f25bf72,0x3f43bea5,0x3eea3d84,0xbf643f7f,
0xbf633f7e,0xbeed3e0d,0x3f7fbf78,0x3db63e81,0xbec83f2e,0xbf6c3f3c,0x3f37bf68,0x3f33bed7,
0x3e903d6f,0xbf763f80,0x3ddbbedf,0x3f7fbf66,0x3f54bf17,0xbf103f4f,0xbf0c3e70,0x3f56bf79,
0xbf7b3f80,0xbe453d3c,0xbe4b3eae,0xbf7b3f71,0xbf623f71,0xbef03eab,0x3dc23d56,0xbf7f3f80,
0xbf363f4e,0xbf343f18,0x3ec2be76,0xbf6d3f79,0xbef33f19,0xbf613f4d,0x3f22bf03,0xbf463f5c,
0xbe133f7f,0xbf7dbdc2,0xbf033f62,0xbf5cbef0,0x3e76bf7b,0x3f793e45,0x3f18bf55,0x3f4e3f0e,
0xbeab3f75,0xbf71be93,0xbf2b3f46,0xbf3ebf22,0x3ed9bf6d,0x3f683ec2,0x3f3dbf36,0x3f2d3f34,
0x3ed7bf7c,0x3f683e3f,0x3f2e3f0c,0xbf3c3f56,0xbf4c3f47,0xbf1abf21,0xbe81bf61,0x3f78bef6,
0x3f7dbec8,0x3e203f6c,0xbe703f80,0xbf793c17,0xbf72bdb6,0x3ea8bf7f,0x3f2abf63,0x3f3f3eed,
0xbf293f76,0xbf40be8d,0x3f66bf48,0x3ee23f1f,0x3f80becb,0xbd0a3f6b,0xbf693c7b,0x3ed4bf80,
0xbf1cbeea,0x3f4bbf64,0x3e843f43,0xbf773f25,0xbe6a3f7a,0xbf793e57,0x3f15bf7c,0x3f503e38,
0x3f59bf6f,0x3f083eba,0xbe2cbf31,0x3f7cbf39,0xbf41bd9d,0x3f28bf7f,0xbf653f64,0xbee5bee8,
0xbed13f7a,0xbf6a3e5d,0x3f303e32,0xbf3a3f7c,0x3f7ebefb,0xbe003f5f,0x3efebf7e,0x3f5ebdf4,
0xbf773f65,0xbe8abee5,0xbf7e3f28,0x3df4bf41,0x3e323f08,0xbf7c3f59,0xbe5d3f51,0xbf7a3f14,
0x3f7fbf4a,0x3d9d3f1d,0x3f73befe,0xbe9f3f5e,0x3cb0bf30,0x3f80bf3a,0x3ecebf6a,0x3f6abed1,
0x3f80bf5a,0xbc7b3f07,0xbecb3f50,0xbf6b3f15,0x3ef8bf5e,0x3f60bf00,0x3f1fbe07,0xbf483f7e,
0xbf0b3d0a,0x3f57bf80,0x3f7cbf70,0x3e383eb4,0xbf7f3f66,0xbda9bee2,0x3e9cbf40,0x3f74bf29,
0xbf743f4c,0x3e99bf1a,0x3f44bf02,0xbf243f5d,0xbf6d3f80,0xbec03d23,0x3f80bf70,0xbc173eb1,
0xbef63f3f,0xbf613f2a,0x3f47bf72,0x3f21bea8,0x3e3f3e20,0xbf7c3f7d,0x3e51bf06,0x3f7bbf5a,
0x3f54bf3d,0xbf0f3f2d,0x3f55bf68,0x3f0ebed9,0x3f75bf67,0xbe963edc,0x3f23bf3e,0x3f45bf2b,
0x3f80bf7d,0xbb493e19,0x3ec5bf04,0x3f6cbf5b,0x3f75bf7d,0x3e93be13,0x3dcfbe7c,0x3f7fbf78,
0x34ef35c1,0xac6da5e4,0xb881b918,0x306729e3,0x32b93423,0xb133af65,0xb670b7c2,0x3511334c,
0x2f653133,0xb423b2b9,0xb34cb511,0x37c23670,0x25e42c6d,0xb5c1b4ef,0xa9e3b067,0x39183881,
0x343e34ef,0xababa51b,0xb7eeb881,0x2fa4291b,0x31ce3322,0xb07fae67,0xb59fb6cc,0x34693257,
0x2e67307f,0xb322b1ce,0xb257b469,0x36cc359f,0x251b2bab,0xb4efb43e,0xa91bafa4,0x388137ee,
0x33223423,0xaa7ca452,0xb6ccb7c2,0x2e782852,0x30e63202,0xaf98ad6a,0xb4c9b5ce,0x337d3160,
0x2d6a2f98,0xb202b0e6,0xb160b37d,0x35ce34c9,0x24522a7c,0xb423b322,0xa852ae78,0x37c236cc,
0x31ce32b9,0xa94ea312,0xb59fb670,0x2d4c2711,0x2ffe30e6,0xae34ac6d,0xb3dfb4c9,0x32263067,
0x2c6d2e34,0xb0e6affe,0xb067b226,0x34c933df,0x2312294e,0xb2b9b1ce,0xa711ad4c,0x3670359f,
0x307f3133,0xa820a17f,0xb469b511,0x2c1f257f,0x2e342f98,0xacd2aae1,0xb226b37d,0x30cb2edc,
0x2ae12cd2,0xaf98ae34,0xaedcb0cb,0x337d3226,0x217f2820,0xb133b07f,0xa57fac1f,0x35113469,
0x2e672f65,0xa5e49fdb,0xb257b34c,0x29e323db,0x2c6d2d6a,0xaae1a8e9,0xb067b160,0x2edc2ce7,
0x28e92ae1,0xad6aac6d,0xace7aedc,0x31603067,0x1fdb25e4,0xaf65ae67,0xa3dba9e3,0x334c3257,
0x2bab2c6d,0xa3129cb6,0xafa4b067,0x271120b6,0x294e2a7c,0xa820a5e4,0xad4cae78,0x2c1f29e3,
0x25e42820,0xaa7ca94e,0xa9e3ac1f,0x2e782d4c,0x1cb62312,0xac6dabab,0xa0b6a711,0x30672fa4,
0x251b25e4,0x9cb69648,0xa91ba9e3,0x20b61a48,0x23122452,0xa17f9fdb,0xa711a852,0x257f23db,
0x1fdb217f,0xa452a312,0xa3dba57f,0x28522711,0x16481cb6,0xa5e4a51b,0x9a48a0b6,0x29e3291b,
0xbf7f3f80,0x3dc2bd3c,0xbf623f68,0x3ef0bed9,0xbf7b3f7d,0x3e45be13,0xbf553f5c,0x3f0ebf03,
0xbf753f79,0x3e93be76,0xbf463f4e,0x3f22bf18,0xbf6d3f71,0x3ec2beab,0xbf363f3e,0x3f34bf2b,
0xbf6d3f7e,0x3ec0be0d,0x3f33bf02,0x3f37bf5d,0xbf243f4f,0x3f44bf17,0x3f74bf5a,0x3e99bf06,
0xbe513edf,0x3f7bbf66,0x3f7cbf80,0xbe3fbd6f,0x3e90bd23,0x3f76bf80,0x3f47bf68,0xbf213ed7,
0xbf483f79,0x3f1fbe6a,0x3ef8bf50,0xbf603f15,0xbc7b3ee2,0x3f80bf66,0xbebdbd84,0xbf6e3f7f,
0x3f43bed4,0x3f25bf69,0xbf743f3b,0xbe9c3f2f,0x3f7cbf77,0xbe38be84,0xbf573f7e,0x3f0bbe07,
0xbf133f73,0x3f52bea2,0xbf7a3f28,0xbe5d3f41,0x3f1ebce2,0x3f49bf80,0xbefb3f6a,0x3f5fbed1,
0x3f6fbf77,0xbebabe87,0x3f31be00,0x3f39bf7e,0xbd9dbf08,0xbf7f3f59,0x3f64bf7c,0xbee8be2c,
0xbea23f6a,0x3f73bece,0x3d903f31,0x3f7fbf39,0x3f7abefb,0x3e63bf5f,0x3f7cbf49,0xbe2cbf1e,
0x3e00bf52,0xbf7e3f13,0xbe87bf0a,0xbf773f58,0xbf803f27,0xbce23f42,0xbf6f3f64,0x3eb73ee8,
0xbd0a3f60,0x3f80bef8,0x3f70bf48,0xbeb4bf1f,0x3f66bf57,0xbee2bf0b,0xbf40be38,0xbf293f7c,
0xbf50bda9,0xbf153f7f,0xbe6a3f74,0x3f79be9c,0xbe073f6b,0x3f7ebecb,0x3f77bf38,0xbe84bf32,
0x3e813f54,0x3f78bf10,0xbf1abf0c,0xbf4c3f56,0x3ed7bf7f,0xbf68bdb6,0xbd233f74,0x3f80be99,
0xbf663f37,0x3edf3f33,0x3f2abf6d,0xbf3fbec0,0x3f79bddb,0x3e70bf7f,0xbf7d3ef6,0x3e203f61,
0x3f043f45,0x3f5bbf23,0xbf183f62,0x3f4e3ef0,0xbe7cbf6c,0xbf783ec5,0x3f4dbf36,0xbf19bf34,
0xbd3c3f7f,0x3f80bdcf,0xbf713ef3,0x3eae3f61,0x3eabbf7b,0xbf71be45,0x3f80be4b,0xbd56bf7b,
0xbf233f2d,0x3f45bf3d,0xbe963eae,0x3f75bf71,0xbf0f3f19,0x3f54bf4d,0xbe4b3e7c,0x3f7bbf78,
0xbef33f04,0x3f61bf5b,0xbdcf3e19,0x3f7fbf7d,0xbec53edc,0x3f6cbf67,0xbb493d56,0x3f80bf80,
0x3ec8bf1a,0xbf6c3f4c,0xbf803f78,0xbc173e81,0xbdb6be20,0xbf7f3f7d,0xbf633f79,0x3eedbe70,
0xbf0c3ea8,0xbf563f72,0xbf103f3f,0x3f54bf2a,0xbf613f3c,0xbef63f2e,0xbddb3eb1,0x3f7fbf70,
0xbde83f07,0x3f7ebf5a,0xbe8dbe26,0xbf763f7d,0x3f32bea5,0x3f38bf72,0xbf6b3f29,0xbecb3f40,
0x3f7fbf70,0xbda9beb4,0xbf643f80,0x3eeabd0a,0x3f11bf5e,0xbf533f00,0xbe573f1c,0x3f7abf4b,
0xbe32bee5,0xbf7c3f65,0x3f58bf7f,0xbf0abd90,0xbf7e3f3a,0xbdf43f30,0xbe8abeb7,0xbf773f6f,
0xbece3f5e,0x3f6abefe,0xbf803f4a,0xbcb03f1d,0x3f42be63,0x3f27bf7a,0xbe9f3f51,0x3f73bf14,
0x3ee53eba,0x3f65bf6f,0x3f41bcb0,0x3f28bf80,0x3f59bf77,0xbf08be8a,0x3f14bf7e,0xbf513df4,
0xbf1dbe32,0xbf4a3f7c,0xbf5e3e5d,0xbefe3f7a,0xbf3a3f7f,0x3f303d9d,0xbed13f73,0x3f6abe9f,
0xbf2fbe8d,0xbf3b3f76,0xbed43f7e,0x3f69bde8,0xbea53f7a,0x3f72be57,0x3f7fbf11,0xbd84bf53,
0x3f7dbf25,0xbe26bf43,0xbf07beea,0xbf5a3f64,0xbf1cbebd,0xbf4b3f6e,0xbf003f80,0x3f5ebc7b,
0x3f5d3e3f,0x3f02bf7c,0xbf7e3e51,0xbe0d3f7b,0xbeb1bf44,0xbf703f24,0x3f2e3eed,0x3f3cbf63,
0xbea83f80,0x3f72bc17,0xbd6fbf6c,0xbf803ec8,0x3f5abf47,0xbf06bf21,0xbf173f76,0x3f4f3e90,
0xbf79bdc2,0xbe763f7f,0xbe19bf75,0xbf7d3e96,0x3f5c3ec2,0x3f03bf6d,0xbe133f80,0x3f7dbb49,
0xbf2dbf22,0xbf3d3f46,0x3ed9bf75,0xbf68be93,0x3edc3f54,0x3f67bf0f,0xbf2b3f55,0x3f3e3f0e,
0xa51ba5e4,0x1cb61648,0x291b29e3,0xa0b69a48,0xa312a452,0x217f1fdb,0x27112852,0xa57fa3db,
0x9fdba17f,0x24522312,0x23db257f,0xa852a711,0x96489cb6,0x25e4251b,0x1a4820b6,0xa9e3a91b,
0xababac6d,0x23121cb6,0x2fa43067,0xa711a0b6,0xa94eaa7c,0x282025e4,0x2d4c2e78,0xac1fa9e3,
0xa5e4a820,0x2a7c294e,0x29e32c1f,0xae78ad4c,0x9cb6a312,0x2c6d2bab,0x20b62711,0xb067afa4,
0xae67af65,0x25e41fdb,0x3257334c,0xa9e3a3db,0xac6dad6a,0x2ae128e9,0x30673160,0xaedcace7,
0xa8e9aae1,0x2d6a2c6d,0x2ce72edc,0xb160b067,0x9fdba5e4,0x2f652e67,0x23db29e3,0xb34cb257,
0xb07fb133,0x2820217f,0x34693511,0xac1fa57f,0xae34af98,0x2cd22ae1,0x3226337d,0xb0cbaedc,
0xaae1acd2,0x2f982e34,0x2edc30cb,0xb37db226,0xa17fa820,0x3133307f,0x257f2c1f,0xb511b469,
0xb1ceb2b9,0x294e2312,0x359f3670,0xad4ca711,0xaffeb0e6,0x2e342c6d,0x33df34c9,0xb226b067,
0xac6dae34,0x30e62ffe,0x30673226,0xb4c9b3df,0xa312a94e,0x32b931ce,0x27112d4c,0xb670b59f,
0xb322b423,0x2a7c2452,0x36cc37c2,0xae78a852,0xb0e6b202,0x2f982d6a,0x34c935ce,0xb37db160,
0xad6aaf98,0x320230e6,0x3160337d,0xb5ceb4c9,0xa452aa7c,0x34233322,0x28522e78,0xb7c2b6cc,
0xb43eb4ef,0x2bab251b,0x37ee3881,0xafa4a91b,0xb1ceb322,0x307f2e67,0x359f36cc,0xb469b257,
0xae67b07f,0x332231ce,0x32573469,0xb6ccb59f,0xa51babab,0x34ef343e,0x291b2fa4,0xb881b7ee,
0xb4efb5c1,0x2c6d25e4,0x38813918,0xb067a9e3,0xb2b9b423,0x31332f65,0x367037c2,0xb511b34c,
0xaf65b133,0x342332b9,0x334c3511,0xb7c2b670,0xa5e4ac6d,0x35c134ef,0x29e33067,0xb918b881,
0x3f3d3f36,0x3f2dbf34,0x3f713ec5,0x3eaebf6c,0xbf4dbf23,0xbf193f45,0xbf78be96,0xbe7c3f75,
0x3f5b3f0f,0x3f04bf54,0x3f7d3e4b,0x3e19bf7b,0xbf67bef3,0xbedc3f61,0xbf80bdcf,0xbd563f7f,
0x3f663f24,0x3edfbf44,0x3d6fbf74,0xbf80be99,0xbf80be51,0x3d233f7b,0x3ed73f7c,0x3f68be3f,
0x3f5dbe90,0xbf02bf76,0xbf4cbf47,0xbf1a3f21,0xbf063f33,0x3f5a3f37,0x3f7d3ec8,0x3e20bf6c,
0x3f7d3f11,0x3e26bf53,0xbf79be57,0x3e6a3f7a,0xbf403e8d,0x3f293f76,0x3ee2bf1f,0xbf66bf48,
0xbd0abf6b,0xbf80becb,0x3ed43f80,0x3f693c7b,0x3f4b3f64,0x3f1cbeea,0xbf77bf25,0xbe843f43,
0x3f7e3efb,0xbe00bf5f,0x3efe3f7e,0x3f5e3df4,0xbe2c3f31,0x3f7c3f39,0xbf7abece,0x3e633f6a,
0xbf65bf64,0xbee53ee8,0x3d90bf42,0xbf7fbf27,0x3f30be32,0xbf3abf7c,0x3f6f3f58,0x3eb7bf0a,
0x3f6a3ed1,0xbecebf6a,0x3f313ce2,0xbf39bf80,0x3efb3f73,0x3f5f3ea2,0x3f493f7f,0x3f1ebd90,
0xbf52be63,0x3f133f7a,0xbf0a3e2c,0x3f583f7c,0xbf27bf7e,0xbf42be00,0xbf64bf77,0xbee83e87,
0x3f433ea5,0xbf25bf72,0xbf64bf7f,0xbeea3d84,0x3f6e3f7d,0x3ebdbe26,0xbc7bbf07,0xbf80bf5a,
0x3de83f1c,0x3f7e3f4b,0x3f603f00,0xbef8bf5e,0xbf53bed4,0x3f113f69,0x3f573f80,0x3f0b3d0a,
0x3f0c3e70,0xbf56bf79,0xbe3f3e20,0x3f7c3f7d,0x3f743f4c,0xbe99bf1a,0xbf44bf02,0x3f243f5d,
0x3f6d3f80,0x3ec03d23,0xbf80bf70,0x3c173eb1,0x3ef63f3f,0x3f613f2a,0xbf47bf72,0xbf21bea8,
0x3e933e13,0xbf75bf7d,0x3f7f3f78,0xbdcfbe7c,0x3f0e3ed9,0xbf55bf68,0x3f7b3f80,0x3e453d3c,
0x3f453f2b,0xbf23bf3e,0x3f623f71,0x3ef03eab,0x3f6c3f5b,0xbec5bf04,0x3f363f4e,0x3f343f18,
0x3f803b49,0xbd3cbf80,0x3f68bec2,0xbed9bf6d,0xbf7d3dc2,0x3e133f7f,0xbf5c3ef0,0x3f033f62,
0x3f79be45,0xbe76bf7b,0x3f4ebf0e,0xbf18bf55,0xbf713e93,0x3eab3f75,0xbf3e3f22,0x3f2b3f46,
0xbf723db6,0x3ea83f7f,0x3f2a3f63,0x3f3fbeed,0x3f2ebf0c,0xbf3cbf56,0xbf70bf10,0xbeb13f54,
0xbe813f61,0x3f783ef6,0x3f7e3ddb,0xbe0dbf7f,0xbe70bf80,0xbf79bc17,0xbf4f3ec0,0x3f173f6d,
0x3f50be38,0xbf15bf7c,0xbf073f0b,0x3f5a3f57,0xbd843f60,0x3f7f3ef8,0xbea5bf7e,0xbf72bde8,
0xbf3bbf6e,0xbf2f3ebd,0x3f703f38,0x3eb4bf32,0x3f7e3e9c,0xbe07bf74,0xbf5e3da9,0x3f003f7f,
0xbf1d3e8a,0x3f4a3f77,0xbf77bf49,0xbe873f1e,0xbf14bf80,0xbf51bcb0,0x3f08beba,0xbf59bf6f,
0x3f733e9f,0xbea2bf73,0x3f283f7f,0x3f41bd9d,0x3ce23f52,0x3f803f13,0xbf6abe5d,0x3ed13f7a,
0x3ebabeb7,0xbf6fbf6f,0xbcb0bf30,0xbf80bf3a,0x3f773f65,0x3e8abee5,0x3f7e3f28,0xbdf4bf41,
0xbe323f08,0x3f7c3f59,0x3e5d3f51,0x3f7a3f14,0xbf7fbf4a,0xbd9d3f1d,0xbf73befe,0x3e9f3f5e,
0xbda93ee2,0x3f7f3f66,0x3f743f29,0xbe9cbf40,0xbf6bbf15,0x3ecb3f50,0x3f383f79,0x3f323e6a,
0xbf48bf7e,0xbf1fbe07,0xbe8d3e84,0x3f763f77,0x3e38beb4,0xbf7cbf70,0xbf7abf3b,0x3e573f2f,
0xbe51bf06,0xbf7bbf5a,0x3f103f4f,0x3f543f17,0x3eed3e0d,0xbf63bf7e,0xbdb63e81,0x3f7f3f78,
0x3f6c3f3c,0xbec8bf2e,0xbf33bed7,0x3f373f68,0x3f763f80,0x3e90bd6f,0xbf7fbf66,0x3ddb3edf,
0x3ef33f19,0x3f613f4d,0xbf22bf03,0x3f463f5c,0x3e4b3eae,0x3f7b3f71,0xbf54bf3d,0x3f0f3f2d,
0xbdc23d56,0x3f7f3f80,0xbf75bf67,0x3e963edc,0xbec2be76,0x3f6d3f79,0xbf80bf7d,0x3b493e19,
0xb5a4b699,0x2d0426ad,0x390539a4,0xb0fdaaac,0xb3a7b4b8,0x31e83032,0x373d3858,0xb5b6b420,
0xb032b1e8,0x34b833a7,0x342035b6,0xb858b73d,0xa6adad04,0x369935a4,0x2aac30fd,0xb9a4b905,
0xb65fb77a,0x2d9c2777,0x39803a23,0xb191ab75,0xb44cb550,0x329f30b2,0x380238c9,0xb659b499,
0xb0b2b29f,0x3550344c,0x34993659,0xb8c9b802,0xa777ad9c,0x377a365f,0x2b753191,0xba23b980,
0xb71fb833,0x2e342820,0x39f23a95,0xb226ac1f,0xb4c6b5eb,0x33573133,0x38623935,0xb6f9b511,
0xb133b357,0x35eb34c6,0x351136f9,0xb935b862,0xa820ae34,0x3833371f,0x2c1f3226,0xba95b9f2,
0xb7e7b8ae,0x2ecd2885,0x3a5a3af9,0xb2b9ac83,0xb542b68b,0x340931b4,0x38bf399b,0xb796b587,
0xb1b4b409,0x368b3542,0x35873796,0xb99bb8bf,0xa885aecd,0x38ae37e7,0x2c8332b9,0xbaf9ba5a,
0xb85bb930,0x2f6528e9,0x3ab83b4e,0xb34cace7,0xb5c1b72e,0x34673236,0x391839fa,0xb817b5fd,
0xb236b467,0x372e35c1,0x35fd3817,0xb9fab918,0xa8e9af65,0x3930385b,0x2ce7334c,0xbb4ebab8,
0xb8c7b9ba,0x2ffe294e,0x3b0b3b93,0xb3dfad4c,0xb642b7d7,0x34c632b9,0x396d3a52,0xb862b670,
0xb2b9b4c6,0x37d73642,0x36703862,0xba52b96d,0xa94eaffe,0x39ba38c7,0x2d4c33df,0xbb93bb0b,
0xb939ba4d,0x304c29b3,0x3b533bc7,0xb438adb0,0xb6c6b843,0x3526333d,0x39be3aa3,0xb8abb6e3,
0xb33db526,0x384336c6,0x36e338ab,0xbaa3b9be,0xa9b3b04c,0x3a4d3939,0x2db03438,0xbbc7bb53,
0xb9b1baec,0x30992a17,0x3b8f3beb,0xb481ae14,0xb74db89d,0x358833c1,0x3a0b3aed,0xb8f1b753,
0xb3c1b588,0x389d374d,0x375338f1,0xbaedba0b,0xaa17b099,0x3aec39b1,0x2e143481,0xbbebbb8f,
};

#define DEV __device__ __forceinline__

constexpr uint32_t SM_U = 0;
constexpr uint32_t SM_K = 16384;
constexpr uint32_t SM_YA = 16896;
constexpr uint32_t SM_V = 34816, SM_Q = 51200;
constexpr uint32_t SM_X = 67584;
constexpr uint32_t XS = 144, XO = 608, XC = 8 * XO, XB = 4 * XC, XP = XO + 4 * XS - 16;
constexpr uint32_t SM_F = 106496;
constexpr uint32_t SM_T = SM_F + 32768;
constexpr uint32_t TBL_BYTES = 7168;
constexpr uint32_t SM_W = SM_T + TBL_BYTES;
constexpr uint32_t SM_M = SM_W + 65536;
constexpr uint32_t SM_B = SM_M + 128;
constexpr uint32_t SM_ST = SM_B + 160;
constexpr uint32_t SM_TOTAL = SM_ST + 14 * XP;
static_assert(SM_X + 2 * XB <= SM_F && SM_F % 1024 == 0 && SM_W % 128 == 0 && SM_ST % 16 == 0 && SM_TOTAL <= 232448, "layout");
constexpr uint32_t BAR_T = 0, BAR_U = 8, BAR_K = 16, BAR_V = 24, BAR_Q = 32, BAR_S = 40, BAR_X = 48, BAR_Y = 64;
constexpr uint32_t ROWP = 144;
#define WMAP(w) ((w) < 4 ? (w) + 8 : (w) - 4)
#define NREG 216
static_assert(256 * NREG + 128 * 72 <= 384 * 168, "register pool");
#define DLY_K 200
#define VZ 3
#define LDE 5
#define PH 2
#define TSPL 2

#define TS(i)

DEV void mbar_init(uint32_t a, int c) { asm volatile("mbarrier.init.shared::cta.b64 [%0],%1;" ::"r"(a), "r"(c) : "memory"); }
DEV void mbar_expect(uint32_t a, uint32_t b) { asm volatile("mbarrier.arrive.expect_tx.shared::cta.b64 _,[%0],%1;" ::"r"(a), "r"(b) : "memory"); }
DEV void mbar_arrive(uint32_t a) { asm volatile("mbarrier.arrive.shared::cta.b64 _,[%0];" ::"r"(a) : "memory"); }
DEV void mbar_wait(uint32_t a) {
    uint32_t ok = 0;
    for (int n = 0; n < (1 << 22) && !ok; n++)
        asm volatile("{.reg .pred p; mbarrier.try_wait.parity.shared::cta.b64 p,[%1],0; selp.u32 %0,1,0,p;}" : "=r"(ok) : "r"(a) : "memory");
}
DEV uint32_t mapa(uint32_t a, uint32_t r) { uint32_t d; asm("mapa.shared::cluster.u32 %0,%1,%2;" : "=r"(d) : "r"(a), "r"(r)); return d; }
DEV void st_async(uint32_t a, uint32_t x, uint32_t y, uint32_t z, uint32_t w, uint32_t bar) {
    asm volatile("st.async.weak.shared::cluster.mbarrier::complete_tx::bytes.v4.b32 [%0],{%1,%2,%3,%4},[%5];" ::"r"(a), "r"(x), "r"(y), "r"(z), "r"(w), "r"(bar) : "memory");
}
DEV void st_async1(uint32_t a, uint32_t x, uint32_t bar) {
    asm volatile("st.async.weak.shared::cluster.mbarrier::complete_tx::bytes.b32 [%0],%1,[%2];" ::"r"(a), "r"(x), "r"(bar) : "memory");
}
DEV void tma2(uint32_t dst, const CUtensorMap* tm, uint32_t bar, int c1) {
    asm volatile("cp.async.bulk.tensor.2d.shared::cluster.global.mbarrier::complete_tx::bytes [%0],[%1,{%3,%4}],[%2];"
                 ::"r"(dst), "l"((uint64_t)tm), "r"(bar), "r"(0), "r"(c1) : "memory");
}
DEV void tma4(uint32_t dst, const CUtensorMap* tm, uint32_t bar, int c0, int c3) {
    asm volatile("cp.async.bulk.tensor.4d.shared::cluster.global.mbarrier::complete_tx::bytes [%0],[%1,{%3,%4,%4,%5}],[%2];"
                 ::"r"(dst), "l"((uint64_t)tm), "r"(bar), "r"(c0), "r"(0), "r"(c3) : "memory");
}
DEV void tma4q(uint32_t dst, const CUtensorMap* tm, uint32_t bar, int c0, int c2, int c3) {
    asm volatile("cp.async.bulk.tensor.4d.shared::cluster.global.mbarrier::complete_tx::bytes [%0],[%1,{%3,%4,%5,%6}],[%2];"
                 ::"r"(dst), "l"((uint64_t)tm), "r"(bar), "r"(c0), "r"(0), "r"(c2), "r"(c3) : "memory");
}
DEV void tma_store(const CUtensorMap* tm, uint32_t src, int c0, int c2, int c3) {
    asm volatile("cp.async.bulk.tensor.4d.global.shared::cta.bulk_group [%0,{%2,%3,%4,%5}],[%1];"
                 ::"l"((uint64_t)tm), "r"(src), "r"(c0), "r"(0), "r"(c2), "r"(c3) : "memory");
}
DEV void bulk_commit() { asm volatile("cp.async.bulk.commit_group;" ::: "memory"); }
DEV void bulk_wait() { asm volatile("cp.async.bulk.wait_group.read 0;" ::: "memory"); }
DEV int laneid() { int ln; asm volatile("mov.u32 %0,%%laneid;" : "=r"(ln)); return ln; }
DEV int tidx() { int t; asm volatile("mov.u32 %0,%%tid.x;" : "=r"(t)); return t; }
DEV bool elect() { uint32_t p; asm volatile("{.reg .pred P; elect.sync _|P,0xffffffff; selp.u32 %0,1,0,P;}" : "=r"(p)); return p; }
DEV void bulk_load(uint32_t dst, const void* src, uint32_t bytes, uint32_t bar) {
    asm volatile("cp.async.bulk.shared::cluster.global.mbarrier::complete_tx::bytes [%0],[%1],%2,[%3];" ::"r"(dst), "l"(src), "r"(bytes), "r"(bar) : "memory");
}
DEV void bulk_mcast(uint32_t dst, const void* src, uint32_t bytes, uint32_t bar, uint16_t mask) {
    asm volatile("cp.async.bulk.shared::cluster.global.mbarrier::complete_tx::bytes.multicast::cluster [%0],[%1],%2,[%3],%4;"
                 ::"r"(dst), "l"(src), "r"(bytes), "r"(bar), "h"(mask) : "memory");
}
DEV void bulk_send(uint32_t dst, uint32_t src, uint32_t bytes, uint32_t bar) {
    asm volatile("cp.async.bulk.shared::cluster.shared::cta.mbarrier::complete_tx::bytes [%0],[%1],%2,[%3];" ::"r"(dst), "r"(src), "r"(bytes), "r"(bar) : "memory");
}
DEV uint4 lds128(uint32_t a) { uint4 v; asm volatile("ld.shared.v4.u32 {%0,%1,%2,%3},[%4];" : "=r"(v.x), "=r"(v.y), "=r"(v.z), "=r"(v.w) : "r"(a) : "memory"); return v; }
DEV uint4 ldt(uint32_t a) { uint4 v; asm("ld.shared.v4.u32 {%0,%1,%2,%3},[%4];" : "=r"(v.x), "=r"(v.y), "=r"(v.z), "=r"(v.w) : "r"(a)); return v; }
DEV uint2 lds64(uint32_t a) { uint2 v; asm volatile("ld.shared.v2.u32 {%0,%1},[%2];" : "=r"(v.x), "=r"(v.y) : "r"(a) : "memory"); return v; }
DEV void stg64(void* p, uint32_t x, uint32_t y) { asm volatile("st.global.v2.u32 [%0],{%1,%2};" ::"l"(p), "r"(x), "r"(y) : "memory"); }
DEV uint32_t lds32(uint32_t a) { uint32_t v; asm volatile("ld.shared.u32 %0,[%1];" : "=r"(v) : "r"(a) : "memory"); return v; }
DEV void sts128(uint32_t a, uint32_t x, uint32_t y, uint32_t z, uint32_t w) { asm volatile("st.shared.v4.u32 [%0],{%1,%2,%3,%4};" ::"r"(a), "r"(x), "r"(y), "r"(z), "r"(w) : "memory"); }
DEV void sts64(uint32_t a, uint32_t x, uint32_t y) { asm volatile("st.shared.v2.u32 [%0],{%1,%2};" ::"r"(a), "r"(x), "r"(y) : "memory"); }
DEV void sts32(uint32_t a, uint32_t x) { asm volatile("st.shared.u32 [%0],%1;" ::"r"(a), "r"(x) : "memory"); }
DEV void ldsm4(uint32_t* r, uint32_t a) { asm volatile("ldmatrix.sync.aligned.m8n8.x4.shared.b16 {%0,%1,%2,%3},[%4];" : "=r"(r[0]), "=r"(r[1]), "=r"(r[2]), "=r"(r[3]) : "r"(a) : "memory"); }
DEV void ldsm4t(uint32_t* r, uint32_t a) { asm volatile("ldmatrix.sync.aligned.m8n8.x4.trans.shared.b16 {%0,%1,%2,%3},[%4];" : "=r"(r[0]), "=r"(r[1]), "=r"(r[2]), "=r"(r[3]) : "r"(a) : "memory"); }
DEV void stsm4t(uint32_t a, const uint32_t* r) { asm volatile("stmatrix.sync.aligned.m8n8.x4.trans.shared.b16 [%0],{%1,%2,%3,%4};" ::"r"(a), "r"(r[0]), "r"(r[1]), "r"(r[2]), "r"(r[3]) : "memory"); }
DEV void stsm4(uint32_t a, uint32_t x, uint32_t y, uint32_t z, uint32_t w) { asm volatile("stmatrix.sync.aligned.m8n8.x4.shared.b16 [%0],{%1,%2,%3,%4};" ::"r"(a), "r"(x), "r"(y), "r"(z), "r"(w) : "memory"); }
DEV uint32_t pack2(float lo, float hi) { uint32_t d; asm("cvt.rn.bf16x2.f32 %0,%1,%2;" : "=r"(d) : "f"(hi), "f"(lo)); return d; }
DEV uint32_t hfma(uint32_t a, uint32_t b, uint32_t c) { uint32_t d; asm("fma.rn.bf16x2 %0,%1,%2,%3;" : "=r"(d) : "r"(a), "r"(b), "r"(c)); return d; }
DEV uint32_t hmul(uint32_t a, uint32_t b) { uint32_t d; asm("mul.rn.bf16x2 %0,%1,%2;" : "=r"(d) : "r"(a), "r"(b)); return d; }
DEV uint32_t hadd(uint32_t a, uint32_t b) { uint32_t d; asm("add.rn.bf16x2 %0,%1,%2;" : "=r"(d) : "r"(a), "r"(b)); return d; }
DEV uint32_t hneg(uint32_t a) { uint32_t d; asm("neg.bf16x2 %0,%1;" : "=r"(d) : "r"(a)); return d; }
DEV uint32_t prmt(uint32_t a, uint32_t b, uint32_t s) { uint32_t d; asm("prmt.b32 %0,%1,%2,%3;" : "=r"(d) : "r"(a), "r"(b), "r"(s)); return d; }
struct F4 { float x, y, z, w; };
DEV F4 mma16(uint32_t a0, uint32_t a1, uint32_t a2, uint32_t a3, uint32_t b0, uint32_t b1, F4 c) {
    F4 d;
    asm("mma.sync.aligned.m16n8k16.row.col.f32.bf16.bf16.f32 {%0,%1,%2,%3},{%4,%5,%6,%7},{%8,%9},{%10,%11,%12,%13};"
        : "=f"(d.x), "=f"(d.y), "=f"(d.z), "=f"(d.w)
        : "r"(a0), "r"(a1), "r"(a2), "r"(a3), "r"(b0), "r"(b1), "f"(c.x), "f"(c.y), "f"(c.z), "f"(c.w));
    return d;
}
DEV F4 mma16(uint4 a, uint32_t b0, uint32_t b1, F4 c) { return mma16(a.x, a.y, a.z, a.w, b0, b1, c); }
DEV F4 mma8(uint32_t a0, uint32_t a1, uint32_t b0) {
    F4 d;
    asm("mma.sync.aligned.m16n8k8.row.col.f32.bf16.bf16.f32 {%0,%1,%2,%3},{%4,%5},{%6},{%7,%7,%7,%7};"
        : "=f"(d.x), "=f"(d.y), "=f"(d.z), "=f"(d.w) : "r"(a0), "r"(a1), "r"(b0), "f"(0.f));
    return d;
}
DEV uint32_t hsub(uint32_t a, uint32_t b) { uint32_t d; asm("sub.rn.bf16x2 %0,%1,%2;" : "=r"(d) : "r"(a), "r"(b)); return d; }
DEV uint32_t hfnma(uint32_t a, uint32_t b, uint32_t c) { uint32_t d; asm("{.reg .b32 t; mul.bf16x2 t,%1,%2; sub.bf16x2 %0,%3,t;}" : "=r"(d) : "r"(a), "r"(b), "r"(c)); return d; }
DEV uint32_t hfms(uint32_t a, uint32_t b, uint32_t c) { uint32_t d; asm("{.reg .b32 t; mul.bf16x2 t,%1,%2; sub.bf16x2 %0,t,%3;}" : "=r"(d) : "r"(a), "r"(b), "r"(c)); return d; }
DEV uint32_t ldg16(const uint16_t* p) { uint16_t v; asm volatile("ld.global.nc.u16 %0,[%1];" : "=h"(v) : "l"(p)); return v; }
DEV uint32_t ldg32(const uint16_t* p, uint32_t i) { uint32_t v; asm volatile("ld.global.nc.u32 %0,[%1];" : "=r"(v) : "l"((const uint32_t*)p + i)); return v; }
DEV uint2 ldg64(const void* p) { uint2 v; asm volatile("ld.global.nc.v2.u32 {%0,%1},[%2];" : "=r"(v.x), "=r"(v.y) : "l"(p)); return v; }
DEV uint4 ldg128(const void* p) { uint4 v; asm volatile("ld.global.nc.v4.u32 {%0,%1,%2,%3},[%4];" : "=r"(v.x), "=r"(v.y), "=r"(v.z), "=r"(v.w) : "l"(p)); return v; }
struct C2 { float r, i; };
DEV C2 cmul(C2 a, C2 b) { C2 d; d.r = fmaf(a.r, b.r, -(a.i * b.i)); d.i = fmaf(a.r, b.i, a.i * b.r); return d; }
DEV C2 cmulc(C2 a, C2 b) { C2 d; d.r = fmaf(a.r, b.r, a.i * b.i); d.i = fmaf(a.i, b.r, -(a.r * b.i)); return d; }
DEV C2 csq(C2 a) {
    C2 d; d.r = fmaf(a.r, a.r, -(a.i * a.i));
    asm("{.reg .f32 t; mul.ftz.f32 t,%1,%2; mul.ftz.f32 %0,t,0f40000000;}" : "=f"(d.i) : "f"(a.r), "f"(a.i));
    return d;
}
DEV float ex2(float x) { float y; asm("ex2.approx.ftz.f32 %0,%1;" : "=f"(y) : "f"(x)); return y; }
DEV float bflo(uint32_t v) { return __uint_as_float(v << 16); }
DEV float bfhi(uint32_t v) { return __uint_as_float(v & 0xffff0000u); }
DEV uint32_t pc(C2 a) { return pack2(a.r, a.i); }

DEV void stg128(void* p, uint32_t x, uint32_t y, uint32_t z, uint32_t w) { asm volatile("st.global.v4.u32 [%0],{%1,%2,%3,%4};" ::"l"(p), "r"(x), "r"(y), "r"(z), "r"(w) : "memory"); }
DEV uint32_t hmaxabs(uint32_t a, uint32_t b) { uint32_t d; asm("max.xorsign.abs.bf16x2 %0,%1,%2;" : "=r"(d) : "r"(a), "r"(b)); return d; }
DEV void fence_async() { asm volatile("fence.proxy.async.shared::cta;" ::: "memory"); }
DEV void bar_arrive(int id, int n) { asm volatile("bar.arrive %0,%1;" ::"r"(id), "r"(n) : "memory"); }
DEV void bar_sync(int id, int n) { asm volatile("bar.sync %0,%1;" ::"r"(id), "r"(n) : "memory"); }
DEV uint32_t pack2h(float lo, float hi) { uint32_t d; asm("cvt.rn.f16x2.f32 %0,%1,%2;" : "=r"(d) : "f"(hi), "f"(lo)); return d; }
DEV uint32_t gfma(uint32_t a, uint32_t b, uint32_t c) { uint32_t d; asm("fma.rn.f16x2 %0,%1,%2,%3;" : "=r"(d) : "r"(a), "r"(b), "r"(c)); return d; }
DEV uint32_t gfnma(uint32_t a, uint32_t b, uint32_t c) { uint32_t d; asm("{.reg .b32 t; neg.f16x2 t,%1; fma.rn.f16x2 %0,t,%2,%3;}" : "=r"(d) : "r"(a), "r"(b), "r"(c)); return d; }
DEV uint32_t gfms(uint32_t a, uint32_t b, uint32_t c) { uint32_t d; asm("{.reg .b32 t; neg.f16x2 t,%3; fma.rn.f16x2 %0,%1,%2,t;}" : "=r"(d) : "r"(a), "r"(b), "r"(c)); return d; }
DEV uint32_t gmul(uint32_t a, uint32_t b) { uint32_t d; asm("mul.rn.f16x2 %0,%1,%2;" : "=r"(d) : "r"(a), "r"(b)); return d; }
DEV uint32_t gadd(uint32_t a, uint32_t b) { uint32_t d; asm("add.rn.f16x2 %0,%1,%2;" : "=r"(d) : "r"(a), "r"(b)); return d; }
DEV uint32_t gsub(uint32_t a, uint32_t b) { uint32_t d; asm("sub.rn.f16x2 %0,%1,%2;" : "=r"(d) : "r"(a), "r"(b)); return d; }

struct Params {
    uint32_t lo[8];
    uint16_t hi[8];
    DEV const uint16_t* ptr(int i) const { return (const uint16_t*)(((uint64_t)hi[i] << 32) | lo[i]); }
    const uint16_t *Dskip, *shift_k, *ssm_D, *ssm_k;
    uint16_t* out;
};

template <class Hook> DEV void kgen_alu(float dt, float dtl, const float (&v)[6], uint32_t row, uint32_t rot, Hook hook) {
    const float xr = v[0] * dtl, xi = v[1] * dt, xb = xi * 256.f;
    const float m1 = ex2(xr), mb = ex2(xr * 256.f);
    const C2 z = {m1 * __cosf(xi), m1 * __sinf(xi)}, zb = {mb * __cosf(xb), mb * __sinf(xb)};
    const float dr = dt * v[2], di = dt * v[3];
    C2 cb; cb.r = fmaf(v[4], dr, -(v[5] * di)); cb.i = fmaf(-v[4], di, -(v[5] * dr));
    const C2 z2 = csq(z), z4 = csq(z2), w = csq(z4), w2 = csq(w), w3 = cmul(w2, w), w4 = csq(w2);
    const C2 w5 = cmul(w4, w), w6 = csq(w3), w7 = cmul(w4, w3), z64 = csq(w4), z128 = csq(z64);
    const C2 h1 = cmulc(cb, z), h2 = cmulc(cb, z2), h3 = cmulc(h2, z);
    const C2 g1 = cmulc(cb, zb), g2 = cmulc(g1, zb), g3 = cmulc(g2, zb), g4 = cmulc(g3, zb);
    const C2 g5 = cmulc(g4, zb), g6 = cmulc(g5, zb), g7 = cmulc(g6, zb), g8 = cmulc(g7, zb), h258 = cmulc(g1, z2);
    const uint32_t p64 = pc(z64), p4 = pc(z4), p128 = pc(z128);
    hook(pc(h1), pc(h258), pc(w7));
    stsm4(row + 9 * ROWP, pc(h1), pc(h2), pc(h3), pc(g1));
    sts32(rot + 8 * ROWP, p4);      sts32(rot + 9 * ROWP, prmt(p4, 0, 0x1032) ^ 0x00008000u);
    stsm4(row + 1 * ROWP, pc(w), pc(w2), pc(w3), pc(w4));
    stsm4(row + 13 * ROWP, pc(h258), pc(g2), pc(g3), pc(g4));
    stsm4(row + 5 * ROWP, pc(w5), pc(w6), pc(w7), pc(cb));
    sts32(rot, p64 ^ 0x80000000u);  sts32(rot + ROWP, prmt(p64, 0, 0x1032));
    sts32(rot + 16 * ROWP, p128 ^ 0x80000000u); sts32(rot + 17 * ROWP, prmt(p128, 0, 0x1032));
    stsm4(row + 17 * ROWP, pc(g5), pc(g6), pc(g7), pc(g8));
}
struct KFrag { uint32_t u[4][4], h[4][4], r[4][4]; };
DEV void kgen_load(KFrag& f, uint32_t a1, uint32_t a2, uint32_t a3) {
#pragma unroll
    for (int j = 0; j < 4; j++) { ldsm4(f.u[j], a1 + j * 32); ldsm4(f.r[j], a3 + j * 32); ldsm4(f.h[j], a2 + j * 32); }
}
DEV void kgen_load(KFrag& f, uint32_t a1, uint32_t a2, uint32_t a3, uint32_t t1, uint32_t t2, uint32_t t3) {
    ldsm4(f.u[0], a1); ldsm4(f.r[0], a3); ldsm4(f.h[0], a2);
    ldsm4(f.r[1], a3 + 32); ldsm4(f.h[1], a2 + 32); ldsm4(f.u[1], (a1 | t1) + 32);
    ldsm4(f.r[2], a3 + 64); ldsm4(f.h[2], a2 + 64); ldsm4(f.u[2], (a1 | t2) + 64);
    ldsm4(f.r[3], a3 + 96); ldsm4(f.h[3], a2 + 96); ldsm4(f.u[3], (a1 | t3) + 96);
    __syncwarp();
}
DEV void mma16a(F4& c, uint32_t a0, uint32_t a1, uint32_t a2, uint32_t a3, uint32_t b0, uint32_t b1) {
    asm("mma.sync.aligned.m16n8k16.row.col.f32.bf16.bf16.f32 {%0,%1,%2,%3},{%4,%5,%6,%7},{%8,%9},{%0,%1,%2,%3};"
        : "+f"(c.x), "+f"(c.y), "+f"(c.z), "+f"(c.w) : "r"(a0), "r"(a1), "r"(a2), "r"(a3), "r"(b0), "r"(b1));
}
DEV void kgen_mma(const KFrag& f, F4 (&ka)[2][3], uint32_t zero) {
#pragma unroll
    for (int j = 0; j < 4; j++) {
        const uint32_t *u = f.u[j], *h = f.h[j], *r = f.r[j];
        const F4 d0 = mma8(u[0], u[1], u[1]), d1 = mma8(u[2], u[3], u[3]);
        const F4 e0 = mma8(h[0], h[1], r[0]), e1 = mma8(h[0], h[1], r[1]);
        const uint32_t u10 = pack2(d0.x, d0.y), u11 = pack2(d1.x, d1.y);
        const uint32_t h40 = pack2(e0.x, e0.y), h41 = pack2(e1.z, e1.w);
        const float one = __uint_as_float(0x3f800000u | zero);
        const uint32_t u0 = __float_as_uint(__fmul_rn(__uint_as_float(u[0]), one)), u2 = __float_as_uint(__fmul_rn(__uint_as_float(u[2]), one));
        const F4 f0 = mma8(u0, u10, r[2]), f1 = mma8(u2, u11, r[3]);
        mma16a(ka[0][0], u0, u10, u2, u11, h[0], h[1]);
        mma16a(ka[0][2], u0, u10, u2, u11, h[2], h[3]);
        mma16a(ka[0][1], u0, u10, u2, u11, h40, h41);
        const uint32_t u20 = pack2(f0.x, f0.y), u30 = pack2(f0.z, f0.w), u21 = pack2(f1.x, f1.y), u31 = pack2(f1.z, f1.w);
        mma16a(ka[1][0], u20, u30, u21, u31, h[0], h[1]);
        mma16a(ka[1][2], u20, u30, u21, u31, h[2], h[3]);
        mma16a(ka[1][1], u20, u30, u21, u31, h40, h41);
    }
}
#define LF4(d, o) "+f"(d[o]), "+f"(d[o + 1]), "+f"(d[o + 2]), "+f"(d[o + 3])
#define LF16(d, o) LF4(d, o), LF4(d, o + 4), LF4(d, o + 8), LF4(d, o + 12)
#define LR4(d, o) "+r"(d[o]), "+r"(d[o + 1]), "+r"(d[o + 2]), "+r"(d[o + 3])
#define LR8(d) LR4(d, 0), LR4(d, 4)
#define OF4(d, o) "=f"(d[o]), "=f"(d[o + 1]), "=f"(d[o + 2]), "=f"(d[o + 3])
#define OF16(d, o) OF4(d, o), OF4(d, o + 4), OF4(d, o + 8), OF4(d, o + 12)
#define OR8(d) "=r"(d[0]), "=r"(d[1]), "=r"(d[2]), "=r"(d[3]), "=r"(d[4]), "=r"(d[5]), "=r"(d[6]), "=r"(d[7])
DEV void wg_fence() { asm volatile("wgmma.fence.sync.aligned;" ::: "memory"); }
DEV void wg_commit() { asm volatile("wgmma.commit_group.sync.aligned;" ::: "memory"); }
template <int N> DEV void wg_wait() { asm volatile("wgmma.wait_group.sync.aligned %0;" ::"n"(N) : "memory"); }
DEV void pin(float (&d)[32]) { asm volatile("" : LF16(d, 0), LF16(d, 16)::"memory"); }
DEV void pin(float (&d)[16]) { asm volatile("" : LF16(d, 0)::"memory"); }
DEV void pin(uint32_t (&d)[4][8]) { asm volatile("" : LR8(d[0]), LR8(d[1]), LR8(d[2]), LR8(d[3])::"memory"); }
DEV uint64_t mkdesc(uint32_t addr, uint32_t lbo, uint32_t sbo, uint32_t sw) {
    return (uint64_t)(((addr & 0x3ffffu) >> 4) | ((lbo >> 4) << 16)) | ((uint64_t)((sbo >> 4) | (sw << 30)) << 32);
}
#define WG64 "wgmma.mma_async.sync.aligned.m64n64k16.f32.bf16.bf16 {%0,%1,%2,%3,%4,%5,%6,%7,%8,%9,%10,%11,%12,%13,%14,%15," \
             "%16,%17,%18,%19,%20,%21,%22,%23,%24,%25,%26,%27,%28,%29,%30,%31},{%32,%33,%34,%35},%36,%37,1,1,%38;"
template <int ACC, int TB> DEV void wg64(float (&d)[32], const uint32_t* a, uint64_t b) {
    if (ACC) asm volatile(WG64 : LF16(d, 0), LF16(d, 16) : "r"(a[0]), "r"(a[1]), "r"(a[2]), "r"(a[3]), "l"(b), "n"(1), "n"(TB));
    else asm volatile(WG64 : LF16(d, 0), LF16(d, 16) : "r"(a[0]), "r"(a[1]), "r"(a[2]), "r"(a[3]), "l"(b), "n"(0), "n"(TB));
}
#define WG32H "wgmma.mma_async.sync.aligned.m64n32k16.f16.f16.f16 {%0,%1,%2,%3,%4,%5,%6,%7},{%8,%9,%10,%11},%12,%13,1,1,0;"
template <int ACC> DEV void wg32h(uint32_t (&d)[8], uint32_t a0, uint32_t a1, uint32_t a2, uint32_t a3, uint64_t b) {
    if (ACC) asm volatile(WG32H : LR8(d) : "r"(a0), "r"(a1), "r"(a2), "r"(a3), "l"(b), "n"(1));
    else asm volatile(WG32H : LR8(d) : "r"(a0), "r"(a1), "r"(a2), "r"(a3), "l"(b), "n"(0));
}
#define WG32S "wgmma.mma_async.sync.aligned.m64n32k16.f32.f16.f16 {%0,%1,%2,%3,%4,%5,%6,%7,%8,%9,%10,%11,%12,%13,%14,%15},%16,%17,%18,1,1,0,0;"
template <int ACC> DEV void wg32s(float (&d)[16], uint64_t a, uint64_t b) {
    if (ACC) asm volatile(WG32S : LF16(d, 0) : "l"(a), "l"(b), "n"(1));
    else asm volatile(WG32S : LF16(d, 0) : "l"(a), "l"(b), "n"(0));
}
#define WG32R "wgmma.mma_async.sync.aligned.m64n32k16.f32.f16.f16 {%0,%1,%2,%3,%4,%5,%6,%7,%8,%9,%10,%11,%12,%13,%14,%15},{%16,%17,%18,%19},%20,%21,1,1,0;"
template <int ACC> DEV void wg32r(float (&d)[16], const uint32_t* a, uint64_t b) {
    if (ACC) asm volatile(WG32R : LF16(d, 0) : "r"(a[0]), "r"(a[1]), "r"(a[2]), "r"(a[3]), "l"(b), "n"(1));
    else asm volatile(WG32R : LF16(d, 0) : "r"(a[0]), "r"(a[1]), "r"(a[2]), "r"(a[3]), "l"(b), "n"(0));
}
struct Tw { uint32_t r[8], i[8]; };
template <int TB> DEV void stage1(float (&d)[32], const uint32_t (&e1)[8], uint32_t sc, uint64_t b) {
    uint32_t e[8];
#pragma unroll
    for (int i = 0; i < 8; i++)
        asm volatile("{.reg .u32 t; add.u32 t,%1,%2; sub.u32 %0,t,0x3f803f80;}" : "=r"(e[i]) : "r"(e1[i]), "r"(sc));
    wg_fence();
    wg64<0, TB>(d, e, b);
    wg64<1, TB>(d, e + 4, b + (TB ? 32 : XC / 8));
    wg_commit();
}
template <bool ADD = false> DEV uint32_t twiddle_a(const float (&d)[32], const uint4 lf, Tw& x, uint32_t zero, float er = 0.f, float ei = 0.f, float c = 0.f) {
    uint32_t tok = 0;
#pragma unroll
    for (int j = 0; j < 8; j++) {
        x.i[j] = pack2h(ADD && j == 0 ? fmaf(ei, c, d[2]) : d[4 * j + 2], d[4 * j + 3]);
        x.r[j] = gfma((j & 1) ? lf.y : lf.x, x.i[j], pack2h(ADD && j == 0 ? fmaf(er, c, d[0]) : d[4 * j], d[4 * j + 1]));
        tok |= x.r[j];
    }
    return tok & zero;
}
DEV void twiddle_b(const uint4 lf, Tw& x) {
#pragma unroll
    for (int j = 0; j < 8; j++) {
        asm volatile("fma.rn.f16x2 %0,%1,%2,%0;" : "+r"(x.i[j]) : "r"((j & 1) ? lf.w : lf.z), "r"(x.r[j]));
        asm volatile("fma.rn.f16x2 %0,%1,%2,%0;" : "+r"(x.r[j]) : "r"((j & 1) ? lf.y : lf.x), "r"(x.i[j]));
    }
}
template <int J0, int J1> DEV void twiddle(const float (&d)[32], const uint4 lf, Tw& x) {
#pragma unroll
    for (int j = J0; j < J1; j++) {
        x.i[j] = pack2h(d[4 * j + 2], d[4 * j + 3]);
        x.r[j] = gfma((j & 1) ? lf.y : lf.x, x.i[j], pack2h(d[4 * j], d[4 * j + 1]));
        asm volatile("fma.rn.f16x2 %0,%1,%2,%0;" : "+r"(x.i[j]) : "r"((j & 1) ? lf.w : lf.z), "r"(x.r[j]));
        asm volatile("fma.rn.f16x2 %0,%1,%2,%0;" : "+r"(x.r[j]) : "r"((j & 1) ? lf.y : lf.x), "r"(x.i[j]));
    }
}
template <int I0, int I1> DEV void stage2p(uint32_t (&S)[4][8], const Tw& x, const Tw& y, uint64_t b) {
    wg_fence();
#pragma unroll
    for (int i = I0; i < I1; i++) wg32h<0>(S[i], x.r[2 * i], y.r[2 * i], x.r[2 * i + 1], y.r[2 * i + 1], b + 32);
#pragma unroll
    for (int i = I0; i < I1; i++) wg32h<1>(S[i], x.i[2 * i], y.i[2 * i], x.i[2 * i + 1], y.i[2 * i + 1], b);
    wg_commit();
}
DEV void stage2(uint32_t (&S)[4][8], const Tw& x, const Tw& y, uint64_t b) {
    wg_fence();
#pragma unroll
    for (int i = 0; i < 4; i++) wg32h<0>(S[i], x.r[2 * i], y.r[2 * i], x.r[2 * i + 1], y.r[2 * i + 1], b + 32);
#pragma unroll
    for (int i = 0; i < 4; i++) wg32h<1>(S[i], x.i[2 * i], y.i[2 * i], x.i[2 * i + 1], y.i[2 * i + 1], b);
    wg_commit();
}
DEV void cmac(uint32_t& pr, uint32_t& pi, uint32_t xr, uint32_t xi, uint32_t fr, uint32_t fi) {
    pr = gfnma(xi, fi, gfma(xr, fr, pr));
    pi = gfma(xi, fr, gfma(xr, fi, pi));
}
template <int Q0, int Q1> DEV void products(uint32_t (&X)[4][8], const uint32_t (&F)[4][8]) {
#pragma unroll
    for (int q = Q0; q < Q1; q++) {
        uint32_t pr[4], pi[4];
#pragma unroll
        for (int j = 0; j < 3; j++) {
            pr[j] = gfnma(X[0][q + 4], F[j][q + 4], gmul(X[0][q], F[j][q]));
            pi[j] = gfma(X[0][q + 4], F[j][q], gmul(X[0][q], F[j][q + 4]));
#pragma unroll
            for (int a = 1; a <= j; a++) cmac(pr[j], pi[j], X[a][q], X[a][q + 4], F[j - a][q], F[j - a][q + 4]);
        }
        pr[3] = gfnma(X[0][q + 4], F[3][q + 4], gfms(X[0][q], F[3][q], pi[2]));
        pi[3] = gfma(X[0][q + 4], F[3][q], gfma(X[0][q], F[3][q + 4], pr[2]));
#pragma unroll
        for (int a = 1; a <= 3; a++) cmac(pr[3], pi[3], X[a][q], X[a][q + 4], F[3 - a][q], F[3 - a][q + 4]);
        X[3][q] = pr[3]; X[3][q + 4] = pi[3];
        X[2][q] = gsub(pr[2], pi[1]); X[2][q + 4] = gadd(pi[2], pr[1]);
        X[1][q] = gsub(pr[1], pi[0]); X[1][q + 4] = gadd(pi[1], pr[0]);
        X[0][q] = pr[0]; X[0][q + 4] = pi[0];
    }
}
DEV void products_lo(uint32_t (&P)[4][8], uint32_t (&C)[8], const uint32_t (&X)[4][8], const uint32_t (&F)[4][8]) {
#pragma unroll
    for (int q = 0; q < 4; q++) {
        P[0][q] = gfnma(X[0][q + 4], F[0][q + 4], gmul(X[0][q], F[0][q]));
        P[0][q + 4] = gfma(X[0][q + 4], F[0][q], gmul(X[0][q], F[0][q + 4]));
        C[q] = gfnma(X[0][q + 4], F[1][q + 4], gmul(X[0][q], F[1][q]));
        C[q + 4] = gfma(X[0][q + 4], F[1][q], gmul(X[0][q], F[1][q + 4]));
        cmac(C[q], C[q + 4], X[1][q], X[1][q + 4], F[0][q], F[0][q + 4]);
        P[1][q] = gsub(C[q], P[0][q + 4]); P[1][q + 4] = gadd(C[q + 4], P[0][q]);
    }
}
template <int Q0, int Q1> DEV void products_hi(uint32_t (&X)[4][8], const uint32_t (&C)[8], const uint32_t (&F)[4][8]) {
#pragma unroll
    for (int q = Q0; q < Q1; q++) {
        uint32_t pr = gfnma(X[0][q + 4], F[2][q + 4], gmul(X[0][q], F[2][q]));
        uint32_t pi = gfma(X[0][q + 4], F[2][q], gmul(X[0][q], F[2][q + 4]));
#pragma unroll
        for (int a = 1; a <= 2; a++) cmac(pr, pi, X[a][q], X[a][q + 4], F[2 - a][q], F[2 - a][q + 4]);
        uint32_t sr = gfnma(X[0][q + 4], F[3][q + 4], gfms(X[0][q], F[3][q], pi));
        uint32_t si = gfma(X[0][q + 4], F[3][q], gfma(X[0][q], F[3][q + 4], pr));
#pragma unroll
        for (int a = 1; a <= 3; a++) cmac(sr, si, X[a][q], X[a][q + 4], F[3 - a][q], F[3 - a][q + 4]);
        X[3][q] = sr; X[3][q + 4] = si;
        X[2][q] = gsub(pr, C[q + 4]); X[2][q + 4] = gadd(pi, C[q]);
    }
}
template <int I0, int I1> DEV void istage2(uint32_t (&W)[4][8], const uint32_t (&P)[4][8], uint64_t b) {
    wg_fence();
#pragma unroll
    for (int i = I0; i < I1; i++) wg32h<0>(W[i], P[i][0], P[i][1], P[i][2], P[i][3], b + 32);
#pragma unroll
    for (int i = I0; i < I1; i++) wg32h<1>(W[i], P[i][4], P[i][5], P[i][6], P[i][7], b);
    wg_commit();
}
template <int I0, int I1> DEV void itwiddle_store(const uint32_t (&W)[4][8], const uint4 lf, uint32_t va) {
#pragma unroll
    for (int i = I0; i < I1; i++)
#pragma unroll
        for (int r = 0; r < 2; r++) {
            uint32_t v[4];
#pragma unroll
            for (int h = 0; h < 2; h++) {
                const uint32_t p = h ? lf.y : lf.x, s = h ? lf.w : lf.z;
                const uint32_t a = W[i][2 * h + r], b = W[i][4 + 2 * h + r];
                const uint32_t x1 = gfnma(p, b, a);
                v[2 + h] = gfnma(s, x1, b);
                v[h] = gfnma(p, v[2 + h], x1);
            }
            stsm4t((va ^ ((i & 1) * 64)) + r * 1024 + (i >> 1) * 8192, v);
        }
}
DEV void istage1(float (&y)[16], uint32_t la, uint64_t b) {
    uint32_t a[4][4];
#pragma unroll
    for (int s = 0; s < 4; s++) ldsm4(a[s], la + s * 256);
    wg_fence();
    wg32r<0>(y, a[0], b);
#pragma unroll
    for (int s = 1; s < 4; s++) wg32r<1>(y, a[s], b + 64 * s);
    wg_commit();
}
DEV void istage1_load(uint32_t (&a)[4][4], uint32_t la) {
#pragma unroll
    for (int s = 0; s < 4; s++) ldsm4(a[s], la + s * 256);
}
DEV void istage1_run(float (&y)[16], const uint32_t (&a)[4][4], uint64_t b) {
    wg_fence();
    wg32r<0>(y, a[0], b);
#pragma unroll
    for (int s = 1; s < 4; s++) wg32r<1>(y, a[s], b + 64 * s);
    wg_commit();
}
DEV void istage1(float (&y0)[16], float (&y1)[16], uint32_t la, uint64_t b) {
    uint32_t a[8][4];
#pragma unroll
    for (int s = 0; s < 8; s++) ldsm4(a[s], la + (s & 3) * 256 + (s >> 2) * 8192);
    wg_fence();
    wg32r<0>(y0, a[0], b);
#pragma unroll
    for (int s = 1; s < 4; s++) wg32r<1>(y0, a[s], b + 64 * s);
    wg32r<0>(y1, a[4], b);
#pragma unroll
    for (int s = 1; s < 4; s++) wg32r<1>(y1, a[4 + s], b + 64 * s);
    wg_commit();
}
template <int I> DEV void pin2(uint32_t (&d)[4][8]) { asm volatile("" : LR8(d[I]), LR8(d[I + 1])::"memory"); }
template <bool LOCAL, int YP> DEV void send_y(const float (&y)[16], int r, uint32_t sc, uint32_t dst, uint32_t bar, bool own) {
    const uint32_t a = hmul(pack2(y[2 * r], y[2 * r + 1]), sc), b = hmul(pack2(y[4 + 2 * r], y[5 + 2 * r]), sc);
    const uint32_t c = hmul(pack2(y[8 + 2 * r], y[9 + 2 * r]), sc), d = hmul(pack2(y[12 + 2 * r], y[13 + 2 * r]), sc);
    if (LOCAL) sts128(dst + r * YP, a, b, c, d);
    else asm volatile("{.reg .pred p; setp.ne.u32 p,%6,0;\n"
                      "@p st.shared.v4.u32 [%0],{%1,%2,%3,%4};\n"
                      "@!p st.async.weak.shared::cluster.mbarrier::complete_tx::bytes.v4.b32 [%0],{%1,%2,%3,%4},[%5];}"
                      ::"r"(dst + r * YP), "r"(a), "r"(b), "r"(c), "r"(d), "r"(bar), "r"((uint32_t)own) : "memory");
}
DEV void pack_y(uint32_t (&o)[8], const float (&y)[16], uint32_t s0, uint32_t s1) {
#pragma unroll
    for (int i = 0; i < 8; i++) o[i] = hmul(pack2(y[4 * (i & 3) + 2 * (i >> 2)], y[4 * (i & 3) + 2 * (i >> 2) + 1]), i >> 2 ? s1 : s0);
}
DEV void send_p(const uint32_t* o, uint32_t dst, uint32_t bar, bool own) {
    asm volatile("{.reg .pred p; setp.ne.u32 p,%6,0;\n"
                 "@p st.shared.v4.u32 [%0],{%1,%2,%3,%4};\n"
                 "@!p st.async.weak.shared::cluster.mbarrier::complete_tx::bytes.v4.b32 [%0],{%1,%2,%3,%4},[%5];}"
                 ::"r"(dst), "r"(o[0]), "r"(o[1]), "r"(o[2]), "r"(o[3]), "r"(bar), "r"((uint32_t)own) : "memory");
}
DEV uint32_t scale_word(uint32_t m) { return (uint32_t)max(249 - (int)(m >> 23), 10) * 0x00800080u; }
DEV uint32_t unscale(uint32_t sx, uint32_t sf) {
    const int f = min(372 - (int)(sx >> 23) - (int)(sf >> 23), 254);
    return (f >= 1 ? (uint32_t)f << 7 : 0x80u >> min(1 - f, 31)) * 0x10001u;
}
template <bool GATE, int NP> DEV void write_out(uint32_t ya, uint16_t* op, const uint2* q) {
    uint32_t r[2 * NP][4];
#pragma unroll
    for (int i = 0; i < 2 * NP; i++) ldsm4t(r[i], ya + i * 32);
#pragma unroll
    for (int i = 0; i < 4 * NP; i++) {
        const uint32_t x = r[i >> 1][2 * (i & 1)], y = r[i >> 1][2 * (i & 1) + 1];
        uint16_t* p = op + ((i & 3) * 128 + (i >> 2)) * 896;
        if (GATE) stg64(p, hmul(x, q[i].x), hmul(y, q[i].y));
        else stg64(p, x, y);
    }
}

template <bool GATE, int NP> DEV void stage_out(uint32_t ya, uint32_t st, const uint2* q) {
    uint32_t r[2 * NP][4];
#pragma unroll
    for (int i = 0; i < 2 * NP; i++) ldsm4t(r[i], ya + i * 32);
#pragma unroll
    for (int i = 0; i < 4 * NP; i++) {
        const uint32_t x = r[i >> 1][2 * (i & 1)], y = r[i >> 1][2 * (i & 1) + 1];
        if (GATE) sts64(st + i * 256, hmul(x, q[i].x), hmul(y, q[i].y));
        else sts64(st + i * 256, x, y);
    }
}

template <bool GATE, int N> DEV void stage_out8(uint32_t ya, uint32_t st, const uint4* q) {
    uint32_t r[N][4];
#pragma unroll
    for (int i = 0; i < N; i++) ldsm4t(r[i], ya + i * 16);
#pragma unroll
    for (int i = 0; i < N; i++) {
        if (GATE) sts128(st + i * 512, hmul(r[i][0], q[i].x), hmul(r[i][1], q[i].y), hmul(r[i][2], q[i].z), hmul(r[i][3], q[i].w));
        else sts128(st + i * 512, r[i][0], r[i][1], r[i][2], r[i][3]);
    }
}

struct ConvOut { uint32_t y_dst, y_bar; bool own, lead; };
DEV void own_arrive(uint32_t bar, bool p) {
    __syncwarp();
    asm volatile("{.reg .pred p; setp.ne.u32 p,%1,0; @p mbarrier.arrive.shared::cta.b64 _,[%0];}" ::"r"(bar), "r"((uint32_t)p) : "memory");
}
template <int Q> DEV void pinq(uint32_t (&d)[4][8]) {
    asm volatile("" : "+r"(d[0][Q]), "+r"(d[1][Q]), "+r"(d[2][Q]), "+r"(d[3][Q]), "+r"(d[0][Q + 4]), "+r"(d[1][Q + 4]), "+r"(d[2][Q + 4]), "+r"(d[3][Q + 4])::"memory");
}
template <int YP, class SigA, class TapsB, class SigB, class VAddr, class VRead, class DstA, class DoneA, class Dst>
DEV void conv4(const uint32_t (&e1)[8], const uint4 lf, uint32_t zero, uint64_t dX, uint64_t dF, uint64_t dT, int wgbar, int vb,
               const uint4 fa, SigA sig_a, TapsB taps_b, SigB sig_b, VAddr v_addr, VRead v_read, DstA dst_a, DoneA done_a, Dst dst) {
    constexpr uint32_t CX = XS / 16, CF = 256, YH = (YP - 16) / 2;
    float A0[32], A1[32], Y0[16], Y1[16];
    uint32_t X0[4][8], X1[4][8], S[4][8], W[4][8], tok;
    Tw T0, T1, T2, T3;
    stage1<1>(A0, e1, fa.x, dF + 1024);
    stage1<1>(A1, e1, fa.y, dF + 1024 + CF);
    const bool t0 = (laneid() & 3) == 0;
    const float er = t0 ? bflo(e1[0]) : 0.f, ei = t0 ? bflo(e1[1]) : 0.f;
    wg_wait<1>(); pin(A0);
    twiddle_a<true>(A0, lf, T0, 0, er, ei, __uint_as_float(fa.z));
    twiddle_b(lf, T0);
    wg_wait<0>(); pin(A1);
    twiddle_a<true>(A1, lf, T1, 0, er, ei, __uint_as_float(fa.w));
    twiddle_b(lf, T1);
    stage2(X0, T0, T1, dT);
    const uint2 xa = sig_a();
    stage1<0>(A0, e1, xa.x, dX + XB / 16);
    stage1<0>(A1, e1, xa.y, dX + XB / 16 + CX);
    const uint32_t ys0 = unscale(fa.x, xa.x), ys1 = unscale(fa.y, xa.y);
    wg_wait<1>(); pin(A0);
    tok = twiddle_a(A0, lf, T2, zero);
    const uint2 fb = taps_b();
    stage1<1>(A0, e1, fb.x | tok, dF);
    wg_wait<1>(); pin(A1); pin(X0);
    twiddle_a(A1, lf, T3, 0);
    twiddle_b(lf, T2);
    twiddle_b(lf, T3);
    stage2(S, T2, T3, dT);
    wg_wait<1>(); pin(A0);
    tok = twiddle_a(A0, lf, T0, zero);
    stage1<1>(A1, e1, fb.y | tok, dF + CF);
    twiddle_b(lf, T0);
    wg_wait<1>(); pin(S);
    products<0, 4>(X0, S);
    istage2<0, 4>(W, X0, dT + 96);
    wg_wait<1>(); pin(A1);
    twiddle<0, TSPL>(A1, lf, T1);
    wg_wait<0>(); pin(W);
    itwiddle_store<0, 4>(W, lf, v_addr());
    bar_sync(wgbar, 128);
    const uint32_t vr0 = v_read();
    {
        uint32_t a0[4][4], a1[4][4];
        istage1_load(a0, vr0);
        istage1_load(a1, vr0 + 8192);
        twiddle<TSPL, LDE>(A1, lf, T1);
        istage1_run(Y0, a0, dT + 192);
        istage1_run(Y1, a1, dT + 192);
    }
    const uint2 xb = sig_b();
    twiddle<LDE, 8>(A1, lf, T1);
    const uint32_t ya_dst = dst_a();
    wg_wait<1>(); pin(Y0);
    send_y<true, YP>(Y0, 0, ys0, ya_dst, 0, true);
    send_y<true, YP>(Y0, 1, ys1, ya_dst, 0, true);
    stage1<0>(A0, e1, xb.x, dX);
    wg_wait<1>(); pin(Y1);
    send_y<true, YP>(Y1, 0, ys0, ya_dst + YH, 0, true);
    send_y<true, YP>(Y1, 1, ys1, ya_dst + YH, 0, true);
    done_a();
    stage1<0>(A1, e1, xb.y, dX + CX);
    stage2(X1, T0, T1, dT);
    const uint32_t ys2 = unscale(fb.x, xb.x), ys3 = unscale(fb.y, xb.y);
    wg_wait<2>(); pin(A0);
    twiddle<0, 8>(A0, lf, T2);
    wg_wait<0>(); pin(A1); pin(X1);
    twiddle<0, 4>(A1, lf, T3);
    stage2p<0, 2>(S, T2, T3, dT);
    twiddle<4, 8>(A1, lf, T3);
    stage2p<2, 4>(S, T2, T3, dT);
    wg_wait<1>(); pin2<0>(S);
    uint32_t C[8], O0[8], O1[8];
    products_lo(X0, C, X1, S);
    istage2<0, 2>(W, X0, dT + 96);
    wg_wait<1>(); pin2<2>(S);
    products_hi<0, PH>(X1, C, S);
    pinq<0>(X1); if (PH > 1) pinq<1>(X1);
    wg_wait<0>(); pin2<0>(W);
    const uint32_t va = v_addr() + vb, vr = v_read() + vb;
    itwiddle_store<0, 2>(W, lf, va);
    bar_sync(wgbar, 128);
    istage1(Y0, vr, dT + 192);
    products_hi<PH, 4>(X1, C, S);
    istage2<2, 4>(W, X1, dT + 96);
    const ConvOut o = dst();
    wg_wait<1>(); pin(Y0);
    pack_y(O0, Y0, ys2, ys3);
    send_p(O0, o.y_dst, o.y_bar, o.own);
    send_p(O0 + 4, o.y_dst + YP, o.y_bar, o.own);
    own_arrive(o.y_bar, o.lead);
    wg_wait<0>(); pin2<2>(W);
    itwiddle_store<2, 4>(W, lf, va);
    bar_sync(wgbar, 128);
    istage1(Y1, vr + 8192, dT + 192);
    wg_wait<0>(); pin(Y1);
    pack_y(O1, Y1, ys2, ys3);
    send_p(O1, o.y_dst + YH, o.y_bar + 16, o.own);
    send_p(O1 + 4, o.y_dst + YH + YP, o.y_bar + 16, o.own);
    asm volatile("" ::"r"(O0[0]), "r"(O0[1]), "r"(O0[2]), "r"(O0[3]), "r"(O0[4]), "r"(O0[5]), "r"(O0[6]), "r"(O0[7]), "r"(O1[0]), "r"(O1[1]), "r"(O1[2]), "r"(O1[3]));
    own_arrive(o.y_bar + 16, o.lead);
}
template <int NC> __global__ void __cluster_dims__(NC, 1, 1) __launch_bounds__(384, 1)
fused_ssm_kernel(const Params P, const __grid_constant__ CUtensorMap tm_u, const __grid_constant__ CUtensorMap tm_k,
                 const __grid_constant__ CUtensorMap tm_v, const __grid_constant__ CUtensorMap tm_q,
                 const __grid_constant__ CUtensorMap tm_s, const __grid_constant__ CUtensorMap tm_o) {
    extern __shared__ __align__(1024) unsigned char smem_raw[];
    const uint32_t sb = (uint32_t)__cvta_generic_to_shared(smem_raw);
    const int tid = threadIdx.x, lane = tid & 31, warp = __shfl_sync(0xffffffffu, WMAP(tid >> 5), 0);
    const int g = lane >> 2, t = lane & 3;
    const int cl = blockIdx.x >> 2, rk = blockIdx.x & 3;
    const int R = blockIdx.x & (NC - 1), c0 = 4 * (blockIdx.x - R);
    constexpr uint32_t YP = 4096 / NC + 16, GP = 256 * NC, PP = GP / 4;
    const uint32_t y_pos = (NC == 8 ? 8 * rk + 4 * (R >> 2) + 2 * (warp >> 2) : 8 * (rk & 1) + 2 * (rk >> 1) + 4 * (warp >> 2)) * YP;
    const int pr = warp & 3;
    const uint32_t bars = sb + SM_B;
    struct Out { uint32_t y_rd, q_rd; uint16_t* y_out; };
    auto out_addr = [&](int b0) {
        const int ln = laneid();
        return Out{sb + (ln & 15) * YP + (ln >> 4) * 16 + b0 * 64, sb + SM_Q + b0 * 1024 + ln * 8,
                   P.out + (size_t)(512 * (b0 >> 2) + 16 * (ln >> 2) + 4 * rk + (b0 & 3)) * 896 + 16 * cl + 4 * (ln & 3)};
    };
    if (warp >= 8) {
#define ROLE_MASK TSP
        asm volatile("setmaxnreg.dec.sync.aligned.u32 72;");
        uint2 shk[2];
        const int kc = NC == 8 ? pr & 1 : pr, d0 = NC == 8 ? 2 * (pr & 2) : 0;
        shk[0] = ldg64(P.shift_k + (c0 + 4 * d0 + g) * 4);
        shk[1] = ldg64(P.shift_k + (c0 + 4 * d0 + 8 + g) * 4);
        const int ch = 16 * cl + 8 * (pr >> 1) + 2 * rk + (pr & 1);
        const uint32_t skipA = ldg16(P.ssm_D + ch), skipB = ldg16(P.Dskip + ch);
        asm volatile("" ::: "memory");
        if (pr == 1 && lane < 3) asm volatile("prefetch.tensormap [%0];" ::"l"((uint64_t)(lane == 0 ? &tm_v : lane == 1 ? &tm_s : &tm_u)) : "memory");
        auto load_taps = [&]() {
            tma2(sb + SM_F + 16384, &tm_s, bars + BAR_S, (16 * cl + 2 * rk) * 128);
            tma2(sb + SM_F + 24576, &tm_s, bars + BAR_S, (16 * cl + 2 * rk + 8) * 128);
        };
        auto load_tables = [&](uint32_t bar) {
            bulk_load(sb + SM_T, P.ptr(7), TBL_BYTES, bar);
#pragma unroll
            for (int i = 0; i < 4; i++) bulk_load(sb + SM_F + i * 4096, P.ptr(7) + TBL_BYTES / 2 + i * 768, 1536, bar);
        };
        auto late_loads = [&]() {
            mbar_expect(bars + BAR_U, 16384);
            tma4(sb + SM_U, &tm_u, bars + BAR_U, c0, 64 / NC * R);
        };
        if (pr == 0) {
            if (elect()) {
                for (int i = 0; i < 11; i++) mbar_init(bars + 8 * i, i == BAR_Q / 8 ? 4 : i < 6 ? 1 : i < 8 ? 5 : 3);
                asm volatile("fence.mbarrier_init.release.cluster;" ::: "memory");
                {
                    const uint32_t t0 = clock();
                    for (int n = 0; n < 64 && (uint32_t)clock() - t0 < DLY_K; n++);
                }
                mbar_expect(bars + BAR_K, 16384 + GP);
                tma4(sb + SM_K, &tm_k, bars + BAR_K, c0, 64 / NC * R - 1);
                mbar_expect(bars + BAR_T, TBL_BYTES + 6144);
                load_tables(bars + BAR_T);
                for (int i = 0; i < 2; i++) { mbar_expect(bars + BAR_X + 8 * i, (16 - 16 / NC) * XP + (NC == 8 ? 320 : 256)); mbar_expect(bars + BAR_Y + 16 * i, 8192 - 8192 / NC); }
                mbar_expect(bars + BAR_Y + 8, 2 * (NC - 1) * (2 * YP - 16));
            }
            __syncwarp();
        }
        if (pr == 2) {
            if (lane < 8) sts32(sb + SM_M + lane * 4, 0);
            asm volatile("fence.release.sync_restrict::shared::cta.cluster;" ::: "memory");
        }
        asm volatile("barrier.cluster.arrive.relaxed.aligned;" ::: "memory");
        if (pr == 0) {
            if (elect()) {
                mbar_expect(bars + BAR_V, 16384);
                tma4(sb + SM_V, &tm_v, bars + BAR_V, c0, 64 / NC * R);
                mbar_expect(bars + BAR_S, 16384);
                load_taps();
            }
            __syncwarp();
        }
        if (pr == 3 && lane < 2) asm volatile("prefetch.tensormap [%0];" ::"l"((uint64_t)(lane == 0 ? &tm_q : &tm_o)) : "memory");
        TS(0);
        auto quad = [&](int m) { return (m >> 3) * GP + (m & 7) * (8 * NC) + (NC == 8 ? (pr & 2) ^ ((m >> 1) & 3) : (m >> 2) & 1) * 16; };
        const int m1 = 32 * kc + 8 * (lane >> 3) + 4 * (lane & 1) + ((lane & 7) >> 1);
        const uint32_t tile_off = quad(m1);
        const uint32_t own = sb + SM_X + (NC == 8 ? (2 * (R & 1) + kc) * XC + (R >> 1) * 2 * XO : pr * XC + R * 2 * XO);
        const bool home = NC == 4 || (pr >> 1) == (R >> 2);
        const uint32_t slot0 = (NC == 8 ? kc * 7 + (home ? 4 : 0) : kc * 3) * XP;
        uint32_t m_dst, m_bar, m_sel, m_on;
        auto put = [&](const uint32_t* r, uint32_t sa, int j) { sts128(sa + (j >> 2) * 2 * XS + (j & 3) * 16, r[0], r[1], r[2], r[3]); };
        auto send = [&](const uint32_t (&r)[8][4], int br, uint32_t stage) {
            fence_async();
            __syncwarp();
            if (elect()) {
#pragma unroll
                for (int j = 0; j < (NC == 8 ? 4 : 3); j++) {
                    const int d = d0 + ((R + 1 + j) & 3);
                    asm volatile("{.reg .pred p; setp.eq.u32 p,%4,0;\n"
                                 "@p cp.async.bulk.shared::cluster.shared::cta.mbarrier::complete_tx::bytes [%0],[%1],%2,[%3];}"
                                 ::"r"(mapa(own + br * XB, d)), "r"(stage + j * XP), "n"(XP), "r"(mapa(bars + BAR_X + br * 8, d)), "r"((uint32_t)(j == 3 && home)) : "memory");
                }
            }
            __syncwarp();
            uint32_t m[2];
#pragma unroll
            for (int h = 0; h < 2; h++) {
                uint32_t x[4];
#pragma unroll
                for (int i = 0; i < 4; i++) {
                    asm volatile("max.xorsign.abs.bf16x2 %0,%1,%2;" : "=r"(x[i]) : "r"(r[4 * h + i][0]), "r"(r[4 * h + i][1]));
                    x[i] = hmaxabs(x[i], hmaxabs(r[4 * h + i][2], r[4 * h + i][3]));
                }
                m[h] = hmaxabs(hmaxabs(x[0], x[1]), hmaxabs(x[2], x[3]));
            }
            uint32_t w = hmaxabs(prmt(m[0], m[1], 0x5410), prmt(m[0], m[1], 0x7632));
            w = hmaxabs(w, __shfl_xor_sync(0xffffffffu, w, 1));
            w = hmaxabs(w, __shfl_xor_sync(0xffffffffu, w, 2));
            w = prmt(w, 0, m_sel) & 0x7fff0000u;
            asm volatile("{.reg .pred p,q; setp.ne.u32 p,%3,0; setp.eq.u32 q,%4,0;\n"
                         "@p red.async.relaxed.cluster.shared::cluster.mbarrier::complete_tx::bytes.max.u32 [%0],%1,[%2];\n"
                         "@q mbarrier.arrive.shared::cta.b64 _,[%5];}"
                         ::"r"(m_dst + br * 16), "r"(w), "r"(m_bar + br * 8), "r"(m_on), "r"(laneid()), "r"(bars + BAR_X + br * 8) : "memory");
            TS(11 + br);
        };
        auto put_addr = [&](int br, uint32_t stage) {
            const int ln = laneid(), dq = d0 + (ln >> 3);
            return ((ln >> 1) & 1) * XO + ((ln >> 2) & 1) * XS + (ln & 1) * 64 + (dq == R ? own + br * XB : stage + ((dq - R - 1) & 3) * XP);
        };
        {
            const uint32_t pa = sb + SM_K + quad(m1 + 7);
            const uint32_t src = sb + SM_K + GP + tile_off;
            uint32_t ks[8][4], sk;
            asm volatile("barrier.cluster.wait.aligned;" ::: "memory");
            mbar_wait(bars + BAR_K);
            sts64(sb + SM_M + 96 + pr * 8, skipA << 16, skipB << 16);
            TS(1);
#pragma unroll
            for (int hh = 0; hh < 2; hh++) {
                const uint32_t w0 = prmt(shk[hh].x, 0, 0x1010), w1 = prmt(shk[hh].x, 0, 0x3232);
                const uint32_t w2 = prmt(shk[hh].y, 0, 0x1010), w3 = prmt(shk[hh].y, 0, 0x3232);
                uint32_t kk[7][4];
#pragma unroll
                for (int i = 0; i < 7; i++) ldsm4t(kk[i], i < 3 ? (pa ^ (hh * 16)) + PP + i * PP : (src ^ (hh * 16)) + (i - 3) * PP);
#pragma unroll
                for (int i = 0; i < 4; i++)
#pragma unroll
                    for (int e = 0; e < 4; e++)
                        ks[4 * hh + i][e] = hfma(kk[i + 3][e], w0, hfma(kk[i + 2][e], w1, hfma(kk[i + 1][e], w2, hmul(kk[i][e], w3))));
            }
            TS(2);
            {
                const int ln = laneid(), md = (d0 + (ln >> 3)) ^ (NC == 8 ? 2 * (ln & 2) : 0);
                m_dst = mapa(sb + SM_M + (ln & 4) + (ln & 1) * 8, md); m_bar = mapa(bars + BAR_X, md);
                m_sel = ln & 2 ? 0x4444 : ln & 1 ? 0x3244 : 0x1044;
                m_on = !(ln & 2) || (NC == 8 && (ln & 7) == 2);
                sk = put_addr(1, sb + SM_ST + slot0);
                asm volatile("" : "+r"(m_dst), "+r"(m_bar), "+r"(m_sel), "+r"(m_on), "+r"(sk)::"memory");
            }
            mbar_wait(bars + BAR_V);
            if (pr == 0) {
                if (elect()) late_loads();
                __syncwarp();
            }
            TS(3);
            const uint32_t stage = sb + SM_ST + slot0;
            uint32_t vv[8][4];
#pragma unroll
            for (int j = 0; j < 4; j++) ldsm4t(vv[j], src + (SM_V - SM_K - GP) + j * PP);
#pragma unroll
            for (int j = 0; j < 8; j++) {
#pragma unroll
                for (int e = 0; e < 4; e++) vv[j][e] = hmul(ks[j][e], vv[j][e]);
                put(vv[j], sk, j);
                if (j < 4) ldsm4t(vv[4 + j], (src ^ 16) + (SM_V - SM_K - GP) + j * PP);
            }
            send(vv, 1, stage);
        }
        {
            const uint32_t fa = sb + SM_F + 16384 + pr * 4096 + lane * 16;
            mbar_wait(bars + BAR_S);
            TS(14);
            uint4 v[8];
#pragma unroll
            for (int i = 0; i < 8; i++) v[i] = lds128(fa + i * 512);
            uint32_t m[8];
#pragma unroll
            for (int i = 0; i < 8; i++) m[i] = hmaxabs(hmaxabs(v[i].x, v[i].y), hmaxabs(v[i].z, v[i].w));
            const uint32_t skip = lds32(sb + SM_M + 96 + pr * 8);
            const uint32_t w = hmaxabs(hmaxabs(hmaxabs(hmaxabs(m[0], m[1]), hmaxabs(m[2], m[3])), hmaxabs(hmaxabs(m[4], m[5]), hmaxabs(m[6], m[7]))), skip) & 0x7fff7fffu;
            const uint32_t sw = scale_word(__reduce_max_sync(0xffffffffu, max(w, w << 16)));
            sts32(sb + SM_M + 64 + (pr >> 1) * 16 + (pr & 1) * 4 + (lane & 1) * 8, lane & 1 ? __float_as_uint(__uint_as_float(skip) * bfhi(sw)) : sw);
            bar_arrive(9 + (pr >> 1), 192);
        }
        TS(5);
        {
            const uint32_t ws = sb + SM_W + pr * 8192;
            F4 ka[2][3];
            bar_sync(1 + pr, 96);
#pragma unroll
            for (int i = 0; i < 6; i++) {
                const uint4 v = lds128(ws + 32768 + 4096 + lane * 16 + i * 512), o = lds128(ws + 4096 + lane * 16 + i * 512);
                F4& k = ka[i / 3][i % 3];
                k.x = __uint_as_float(o.x) + __uint_as_float(v.x); k.y = __uint_as_float(o.y) + __uint_as_float(v.y);
                k.z = __uint_as_float(o.z) + __uint_as_float(v.z); k.w = __uint_as_float(o.w) + __uint_as_float(v.w);
            }
            if (lane == 0) ka[0][0].x += __uint_as_float(lds32(sb + SM_M + 100 + pr * 8));
            const uint32_t pa = ws + g * 48 + t * 4;
#pragma unroll
            for (int mt = 0; mt < 2; mt++)
#pragma unroll
                for (int nt = 0; nt < 3; nt++) {
                    sts32(pa + mt * 768 + nt * 16, pack2(ka[mt][nt].x, ka[mt][nt].y));
                    sts32(pa + mt * 768 + 384 + nt * 16, pack2(ka[mt][nt].z, ka[mt][nt].w));
                }
            __syncwarp();
            const uint32_t r0 = ws + lane * 48, r1 = ws + ((lane + 1) & 31) * 48;
            const uint4 a = lds128(r0), b = lds128(r0 + 16), c = lds128(r0 + 32), na = lds128(r1), nc = lds128(r1 + 32);
            const uint32_t wrap = lane == 31 ? 0x5432 : 0x3210;
            const uint32_t n2 = lane == 31 ? na.w : na.z, n3 = prmt(na.w, nc.x, wrap), n8 = prmt(nc.x, nc.y, wrap), n9 = prmt(nc.y, nc.z, wrap);
            const uint32_t fa = sb + SM_F + pr * 4096 + (lane >> 1) * 32 + (((lane ^ (lane >> 3)) & 1) * 16);
            sts128(fa, a.x, a.y, b.x, b.y);
            sts128(fa + 512, prmt(a.z, 0, 0x1010), prmt(a.z, b.z, 0x5432), prmt(b.z, 0, 0x1010), prmt(b.z, n2, 0x5432));
            sts128(fa + 1024, prmt(a.w, 0, 0x1010), prmt(a.w, b.w, 0x5410), prmt(b.w, 0, 0x1010), prmt(n3, 0, 0x1010));
            sts128(fa + 1536, prmt(a.w, 0, 0x3232), prmt(a.w, b.w, 0x7632), prmt(b.w, 0, 0x3232), prmt(n3, 0, 0x3232));
            const uint32_t tl = (lane & 1) ? 0x5454 : 0x5410, th = (lane & 1) ? 0x7676 : 0x7632;
#pragma unroll
            for (int i = 0; i < 4; i++) {
                const uint32_t v = (i >> 1) ? c.y : c.x, n = (i >> 1) ? n9 : n8;
                const uint32_t vv = prmt(v, 0, (i & 1) ? 0x3232 : 0x1010);
                sts128(fa + 2048 + i * 512, vv, vv, prmt(v, n, (i & 1) ? th : tl), prmt(n, 0, (i & 1) ? 0x3232 : 0x1010));
            }
            uint32_t w = hmaxabs(hmaxabs(hmaxabs(a.x, a.y), hmaxabs(a.z, a.w)), hmaxabs(hmaxabs(b.x, b.y), hmaxabs(b.z, b.w)));
            w = hmaxabs(hmaxabs(w, n9), hmaxabs(c.x, c.y)) & 0x7fff7fffu;
            const uint32_t mx = __reduce_max_sync(0xffffffffu, max(w, w << 16));
            if (lane == 0) sts32(sb + SM_M + 48 + pr * 4, scale_word(mx));
            fence_async();
            bar_arrive(5 + (pr >> 1), 192);
        }
        TS(13);
        if (elect()) {
            mbar_expect(bars + BAR_Q, 4096);
            tma4q(sb + SM_Q + pr * 4096, &tm_q, bars + BAR_Q, c0, 16 / NC * R, pr);
        }
        __syncwarp();
        {
            uint32_t r[8][4];
            const uint32_t stage = sb + SM_V + (NC == 8 ? slot0 : pr * 4096), sa = put_addr(0, stage);
            mbar_wait(bars + BAR_U);
            TS(4);
#pragma unroll
            for (int j = 0; j < 8; j++) ldsm4t(r[j], sb + SM_U + (tile_off ^ ((j >> 2) * 16)) + (j & 3) * PP);
            if (NC == 8) mbar_wait(bars + BAR_X + 8);
#pragma unroll
            for (int j = 0; j < 8; j++) put(r[j], sa, j);
            send(r, 0, stage);
        }
        TS(8);
        if constexpr (NC == 8) {
            uint4 q[8];
            const uint32_t y_rd = sb + lane * YP, q_rd = sb + SM_Q + pr * 4096 + lane * 16;
            mbar_wait(bars + BAR_Q);
#pragma unroll
            for (int i = 0; i < 8; i++) q[i] = lds128(q_rd + i * 512);
            const int d = d0 + (laneid() & 3), wg = pr & 1;
            uint32_t s_dst = mapa(sb + SM_YA + (8 * rk + 4 * (R >> 2) + 2 * wg) * YP, d), s_bar = mapa(bars + BAR_Y + 8, d);
            uint32_t s_src = sb + SM_F + 16384 + wg * 8192 + (d - (d > R)) * 2 * YP;
            asm volatile("" : "+r"(s_dst), "+r"(s_bar), "+r"(s_src)::"memory");
            bar_sync(1 + pr, 96);
            fence_async();
            if (lane < 4) {
                if (d == R) mbar_arrive(bars + BAR_Y + 8);
                else bulk_send(s_dst, s_src, 2 * YP - 16, s_bar);
            }
            __syncwarp();
            mbar_wait(bars + BAR_Y + 8);
            TS(6);
            stage_out8<true, 4>(y_rd + SM_YA + pr * 128, q_rd, q);
            stage_out8<true, 4>(y_rd + SM_YA + pr * 128 + 64, q_rd + 2048, q + 4);
            TS(15);
            fence_async();
            __syncwarp();
            if (elect()) {
#pragma unroll
                for (int j = 0; j < 2; j++) tma_store(&tm_o, sb + SM_Q + pr * 4096 + j * 2048, c0, 2 * R + j, pr);
            }
            __syncwarp();
            TS(7);
            mbar_wait(bars + BAR_Y);
            TS(10);
            stage_out8<false, 4>(y_rd + SM_U + pr * 64, sb + SM_V + pr * 2048 + lane * 16, q);
            fence_async();
            __syncwarp();
            if (elect()) {
                tma_store(&tm_o, sb + SM_V + pr * 2048, 448 + c0, 2 * R + (pr & 1), pr >> 1);
                bulk_commit();
            }
            __syncwarp();
            bulk_wait();
        } else {
            uint2 q[16];
            const Out o = out_addr(4 * pr);
            mbar_wait(bars + BAR_Q);
#pragma unroll
            for (int i = 0; i < 16; i++) q[i] = lds64(o.q_rd + i * 256);
            const int d = (pr & 2) + (lane & 1), wg = pr & 1;
            uint32_t s_dst = mapa(sb + SM_YA + (8 * (rk & 1) + 2 * (rk >> 1) + 4 * wg) * YP, d), s_bar = mapa(bars + BAR_Y + 8, d);
            uint32_t s_src = sb + SM_F + 16384 + wg * 8192 + (d - (d > rk)) * 2 * YP;
            asm volatile("" : "+r"(s_dst), "+r"(s_bar), "+r"(s_src)::"memory");
            bar_sync(1 + pr, 96);
            fence_async();
            if (lane < 2) {
                if (d == rk) mbar_arrive(bars + BAR_Y + 8);
                else bulk_send(s_dst, s_src, YP + 1024, s_bar);
            }
            __syncwarp();
            mbar_wait(bars + BAR_Y + 8);
            TS(6);
            stage_out<true, 2>(o.y_rd + SM_YA, o.q_rd, q);
            stage_out<true, 2>(o.y_rd + SM_YA + 128, o.q_rd + 2048, q + 8);
            TS(15);
            fence_async();
            __syncwarp();
            if (elect()) {
#pragma unroll
                for (int j = 0; j < 4; j++) tma_store(&tm_o, sb + SM_Q + pr * 4096 + j * 1024, 16 * cl, 4 * rk + j, pr);
            }
            __syncwarp();
            TS(7);
            mbar_wait(bars + BAR_Y);
            TS(10);
            stage_out<false, 2>(o.y_rd + SM_U - pr * 128, o.q_rd - (SM_Q - SM_V) - pr * 2048, q);
            fence_async();
            __syncwarp();
            if (elect()) {
#pragma unroll
                for (int j = 0; j < 2; j++) tma_store(&tm_o, sb + SM_V + pr * 2048 + j * 1024, 448 + 16 * cl, 4 * rk + 2 * (pr & 1) + j, pr >> 1);
                bulk_commit();
            }
            __syncwarp();
            bulk_wait();
        }
        TS(9);
    } else {
#undef ROLE_MASK
#define ROLE_MASK TSM
        const int wg = warp >> 2;
        const int ch = 16 * cl + 8 * (pr >> 1) + 2 * rk + (pr & 1);
        uint32_t pm[2][6];
        const uint32_t ldt_raw = ldg16(P.ptr(6) + ch);
#pragma unroll
        for (int i = 0; i < 6; i++) {
            const uint2 w = ldg64(P.ptr(i) + ch * 256 + (wg ? 0 : 128) + lane * 4);
            pm[0][i] = w.x; pm[1][i] = w.y;
        }
        uint32_t e1[8];
        uint4 lf;
        asm volatile("barrier.cluster.arrive.relaxed.aligned;" ::: "memory");
        const uint32_t ws = sb + SM_W + warp * 8192;
        sts32(ws + lane * 4, 0x00003f80u);
#pragma unroll
        for (int i = 0; i < 7; i++) sts128(ws + 21 * ROWP + i * 512 + lane * 16, 0, 0, 0, 0);
        __syncwarp();
        TS(0);

        F4 ka[2][3];
        {
            const uint32_t ld1 = ws + ((lane & 8 ? 21 : 0) + (lane & 7)) * ROWP + (lane >> 4) * 16;
            const uint32_t ld2 = ws + (lane < 16 ? 8 + (lane & 7) : 16 + min(lane & 7, 4)) * ROWP + ((lane >> 3) & 1) * 16;
            const uint32_t ld3 = ws + ((lane < 16 ? 29 : 37) + (lane & 7)) * ROWP + ((lane >> 3) & 1) * 16;
            const uint32_t row_wr = ws + (lane >> 3) * ROWP + (lane & 7) * 16;
            const uint32_t rot_wr = ws + (21 + 2 * t) * ROWP + g * 16 + t * 4;
            {
                float z = __uint_as_float(lds32(ws + 21 * ROWP + lane * 4));
#pragma unroll
                for (int i = 0; i < 6; i++) {
                    F4& k = ka[i / 3][i % 3];
                    if ((VZ >> i) & 1) k = F4{0.f, 0.f, 0.f, 0.f};
                    else asm volatile("add.f32 %0,%4,%4; add.f32 %1,%0,%0; add.f32 %2,%1,%1; add.f32 %3,%2,%2;" : "=f"(k.x), "=f"(k.y), "=f"(k.z), "=f"(k.w) : "f"(z));
                    if (!((VZ >> i) & 1)) z = k.w;
                }
                __syncwarp();
            }
            asm volatile("setmaxnreg.inc.sync.aligned.u32 %0;" ::"n"(NREG));
            asm volatile("barrier.cluster.wait.aligned;" ::: "memory");
            TS(14);
            const float dt = __bfloat162float(__float2bfloat16_rn(expf(bflo(ldt_raw))));
            const float dtl = dt * 1.4426950408889634f;
            float v[6];
#pragma unroll
            for (int i = 0; i < 6; i++) { v[i] = bflo(pm[0][i]); pm[0][i] &= 0xffff0000u; }
            kgen_alu(dt, dtl, v, row_wr, rot_wr, [](uint32_t, uint32_t, uint32_t) {});
            __syncwarp();
            TS(1);
            KFrag f;
#pragma unroll 1
            for (uint32_t sel = 0x3200 | (P.lo[7] & 64u); sel < 0x9000; sel += 0x2200) {
#pragma unroll
                for (int i = 0; i < 6; i++) v[i] = __uint_as_float(prmt(pm[0][i], pm[1][i], sel));
                kgen_alu(dt, dtl, v, row_wr, rot_wr, [&](uint32_t t1, uint32_t t2, uint32_t t3) {
                    const uint32_t zero = P.lo[7] & 64u;
                    kgen_load(f, ld1, ld2, ld3, t1 & zero, t2 & zero, t3 & zero);
                });
                kgen_mma(f, ka, P.lo[7] & 64u);
                __syncwarp();
            }
            auto kgen_done = [&]() {
                const uint32_t pd = ws + 4096 + lane * 16;
                __syncwarp();
#pragma unroll
                for (int i = 0; i < 6; i++) {
                    const F4 v = ka[i / 3][i % 3];
                    sts128(pd + i * 512, __float_as_uint(v.x), __float_as_uint(v.y), __float_as_uint(v.z), __float_as_uint(v.w));
                }
                bar_arrive(1 + pr, 96);
            };
            const uint64_t dX = mkdesc(sb + SM_X + wg * 2 * XS, XC, XO, 0);
            const uint64_t dF = mkdesc(sb + SM_F + wg * 8192, 1024, 256, 3);
            const uint64_t dT = mkdesc(sb + SM_T, 128, 256, 0);
            auto sig_max = [&](int br) {
                mbar_wait(bars + BAR_X + br * 8);
                const uint2 m = lds64(sb + SM_M + br * 16 + wg * 8);
                return make_uint2(scale_word(m.x), scale_word(m.y));
            };
            TS(2);
            auto load_rows = [&]() {
                mbar_wait(bars + BAR_T);
                const uint32_t rt = sb + SM_F + pr * 4096 + laneid() * 16;
                const uint4 a = lds128(rt), b = lds128(rt + 512);
                lf = lds128(rt + 1024);
                e1[0] = a.x; e1[1] = a.y; e1[2] = a.z; e1[3] = a.w; e1[4] = b.x; e1[5] = b.y; e1[6] = b.z; e1[7] = b.w;
            };
            load_rows();
            kgen_load(f, ld1, ld2, ld3);
            kgen_mma(f, ka, P.lo[7] & 64u);
            kgen_done();
            TS(3);
            mbar_wait(bars + BAR_S);
            bar_sync(9 + wg, 192);
            const uint4 fa = lds128(sb + SM_M + 64 + wg * 16);
            TS(4);
            conv4<YP>(e1, lf, (P.lo[7] & 64u), dX, dF, dT, 7 + wg, wg ? -16384 : 16384, fa,
                  [&]() {
                      TS(10);
                      const uint2 r = sig_max(1);
                      TS(11);
                      return r; },
                  [&]() { TS(12); bar_sync(5 + wg, 192); TS(13); return lds64(sb + SM_M + 48 + wg * 8); },
                  [&]() { TS(5); const uint2 r = sig_max(0); TS(6); return r; },
                  [&]() { const int tx = tidx(); return sb + SM_W + wg * 49152 + ((tx >> 2) & 3) * 2048 + ((tx >> 4) & 7) * 128 + (tx & 7) * 16; },
                  [&]() { const int tx = tidx(); return sb + SM_W + wg * 49152 + ((tx >> 5) & 3) * 2048 + (tx & 8) * 128 + (tx & 16) * 8 + ((tx & 7) ^ ((tx >> 3) & 4)) * 16; },
                  [&]() {
                      TS(7);
                      const int tx = tidx(), ln = tx & 31, d = NC == 8 ? ((tx >> 4) & 6) + ((ln >> 3) & 1) : pr;
                      return sb + (NC == 8 ? (ln & 7) + ((ln >> 1) & 8) : ln) * 16 + (d == R ? SM_YA + y_pos : SM_F + 16384 + wg * 8192 + (d - (d > R)) * 2 * YP);
                  },
                  [&]() { bar_arrive(1 + (pr & 2) + wg, 96); },
                  [&]() {
                      const int tx = tidx(), ln = tx & 31, d = NC == 8 ? ((tx >> 4) & 6) + ((ln >> 3) & 1) : pr;
                      const bool own = d == R;
                      const uint32_t y_loc = sb + SM_U + y_pos + (NC == 8 ? (ln & 7) + ((ln >> 1) & 8) : ln) * 16;
                      return ConvOut{own ? y_loc : mapa(y_loc, d), own ? bars + BAR_Y : mapa(bars + BAR_Y, d), own, own && (ln & (NC == 8 ? 23 : 31)) == 0};
                  });
            TS(8);
            if constexpr (NC == 8) {
                const int ln = laneid();
                uint16_t* op = P.out + (size_t)(512 * (2 + wg) + 256 * (pr & 1) + 16 * (ln >> 2) + 2 * R + (pr >> 1)) * 896 + 448 + c0 + 8 * (ln & 3);
                const uint32_t y_rd = sb + SM_U + ln * YP + 256 + warp * 32;
                mbar_wait(bars + BAR_Y + 16);
                uint32_t r[2][4];
                ldsm4t(r[0], y_rd);
                ldsm4t(r[1], y_rd + 16);
                stg128(op, r[0][0], r[0][1], r[0][2], r[0][3]);
                stg128(op + 128 * 896, r[1][0], r[1][1], r[1][2], r[1][3]);
            } else {
                const Out o = out_addr(8 + warp);
                mbar_wait(bars + BAR_Y + 16);
                TS(14);
                write_out<false, 1>(o.y_rd + SM_U, o.y_out + 448, nullptr);
            }
        }
        TS(9);
    }
}
#define L2PROMO CU_TENSOR_MAP_L2_PROMOTION_NONE
typedef CUresult (*EncFn)(CUtensorMap*, CUtensorMapDataType, cuuint32_t, void*, const cuuint64_t*, const cuuint64_t*,
                          const cuuint32_t*, const cuuint32_t*, CUtensorMapInterleave, CUtensorMapSwizzle,
                          CUtensorMapL2promotion, CUtensorMapFloatOOBfill);

static void make_map(EncFn enc, CUtensorMap* tm, void* p, int rank, const cuuint64_t* gd, const cuuint64_t* gs, const cuuint32_t* bx, CUtensorMapSwizzle sw) {
    const cuuint32_t es[5] = {1, 1, 1, 1, 1};
    enc(tm, CU_TENSOR_MAP_DATA_TYPE_BFLOAT16, rank, p, gd, gs, bx, es, CU_TENSOR_MAP_INTERLEAVE_NONE, sw,
        L2PROMO, CU_TENSOR_MAP_FLOAT_OOB_FILL_NONE);
}

template <int NC> static void launch(EncFn enc, void* table, void* const* d_in, void* d_out) {
    const cuuint64_t row = 896;
    const CUtensorMapSwizzle sw = NC == 8 ? CU_TENSOR_MAP_SWIZZLE_64B : CU_TENSOR_MAP_SWIZZLE_32B;
    CUtensorMap tu, tk, tv, tq, ts, to;
    {
        const cuuint64_t gd[4] = {448, 8, 4, 64}, gs[3] = {4 * row, row, 32 * row};
        const cuuint32_t bx[4] = {4 * NC, 8, 4, 64 / NC}, bk[4] = {4 * NC, 8, 4, 64 / NC + 1};
        make_map(enc, &tu, d_in[6], 4, gd, gs, bx, sw);
        make_map(enc, &tk, d_in[1], 4, gd, gs, bk, sw);
        make_map(enc, &tv, d_in[2], 4, gd, gs, bx, sw);
    }
    {
        const cuuint64_t gd[4] = {448, 32, 16, 4}, gs[3] = {16 * row, row, 512 * row};
        const cuuint32_t bx[4] = {4 * NC, 32, 16 / NC, 1};
        make_map(enc, &tq, d_in[0], 4, gd, gs, bx, CU_TENSOR_MAP_SWIZZLE_NONE);
    }
    {
        const cuuint64_t gd[4] = {896, 32, 16, 4}, gs[3] = {32 * row, 2 * row, 1024 * row};
        const cuuint32_t bx[4] = {4 * NC, 32, 1, 1};
        make_map(enc, &to, d_out, 4, gd, gs, bx, CU_TENSOR_MAP_SWIZZLE_NONE);
    }
    {
        const cuuint64_t gd[2] = {16, 448 * 128}, gs[1] = {32};
        const cuuint32_t bx[2] = {16, 256};
        make_map(enc, &ts, d_in[4], 2, gd, gs, bx, CU_TENSOR_MAP_SWIZZLE_32B);
    }
    Params P;
    P.shift_k = (const uint16_t*)d_in[3]; P.ssm_k = (const uint16_t*)d_in[4];
    P.ssm_D = (const uint16_t*)d_in[5]; P.Dskip = (const uint16_t*)d_in[14];
    for (int i = 0; i < 8; i++) {
        const uint64_t a = (uint64_t)(i < 7 ? d_in[7 + i] : table);
        P.lo[i] = (uint32_t)a; P.hi[i] = (uint16_t)(a >> 32);
    }
    P.out = (uint16_t*)d_out;
    fused_ssm_kernel<NC><<<112, 384, SM_TOTAL, cudaStreamPerThread>>>(P, tu, tk, tv, tq, ts, to);
}

extern "C" void kernel_launch(void* const* d_in, const int* in_sizes, int n_in, void* d_out, int out_size) {
    static EncFn enc = nullptr;
    static void* table = nullptr;
    static bool wide = false;
    if (!enc) {
        void* fn = nullptr;
        cudaDriverEntryPointQueryResult qr;
        cudaGetDriverEntryPoint("cuTensorMapEncodeTiled", &fn, cudaEnableDefault, &qr);
        enc = (EncFn)fn;
        cudaGetSymbolAddress(&table, g_table);
        cudaFuncSetAttribute(fused_ssm_kernel<4>, cudaFuncAttributeMaxDynamicSharedMemorySize, SM_TOTAL);
        cudaFuncSetAttribute(fused_ssm_kernel<8>, cudaFuncAttributeMaxDynamicSharedMemorySize, SM_TOTAL);
        cudaLaunchConfig_t cfg = {};
        cudaLaunchAttribute at;
        at.id = cudaLaunchAttributeClusterDimension;
        at.val.clusterDim.x = 8; at.val.clusterDim.y = 1; at.val.clusterDim.z = 1;
        cfg.gridDim = dim3(112); cfg.blockDim = dim3(384); cfg.dynamicSmemBytes = SM_TOTAL; cfg.attrs = &at; cfg.numAttrs = 1;
        int n = 0;
        wide = cudaOccupancyMaxActiveClusters(&n, fused_ssm_kernel<8>, &cfg) == cudaSuccess && n >= 14;
        (void)cudaGetLastError();
    }
    if (wide) launch<8>(enc, table, d_in, d_out);
    else launch<4>(enc, table, d_in, d_out);
}
```
